```python
import torch

def _softmax(x, axis=-1):
    return torch.softmax(x, dim=axis)
def _gelu(x):
    return torch.nn.functional.gelu(x, approximate="tanh")
def _silu(x):
    return torch.nn.functional.silu(x)
def _sigmoid(x):
    return torch.sigmoid(x)
def _layernorm(x, axis=-1, eps=1e-5):
    m = x.mean(dim=axis, keepdim=True)
    v = x.var(dim=axis, keepdim=True, unbiased=False)
    return (x - m) / torch.sqrt(v + eps)
def _scatter_add(tgt, idx, src, axis=0):
    return tgt.clone().index_add_(axis, idx, src)
def _segment_sum(src, seg, n):
    out = torch.zeros((n,) + src.shape[1:], dtype=src.dtype)
    return out.index_add_(0, seg, src)
def _pad(x, pw):
    flat = tuple(v for pair in reversed(pw) for v in pair)
    return torch.nn.functional.pad(x, flat)

kernel_name = 'standalone__channel_attn_eca__vision'

def setup_inputs():

    _w = (lambda a: (lambda t: t.to(torch.bfloat16) if t.is_floating_point() else t)(torch.as_tensor(a)))
    H = W = 384
    C = 384
    k = 1
    return {
        "x": _w((lambda *s: torch.randn(*s, dtype=torch.bfloat16) * 1.6)(1, H, W, C) + (lambda *s: torch.randn(*s, dtype=torch.bfloat16) * 1.6)(1, 1, 1, C) * 2.0),
        "w1d": _w((lambda *s: torch.randn(*s, dtype=torch.bfloat16) * 1.6)(k)),
    }

def reference(x, w1d):
    B, H, W, C = x.shape
    k = 1
    pad = k // 2
    g = torch.einsum("bhwc->bc", x) / (H * W)
    gp = _pad(g, ((0, 0), (pad, pad)))
    s = torch.zeros_like(g)
    for i in range(k):
        s = s + gp[:, i:i + C] * w1d[i]
    s = _sigmoid(s)
    return x * s[:, None, None, :]
```

```cpp
#include <cuda_runtime.h>
#include <cuda_bf16.h>
#include <stdint.h>
#include <string.h>

namespace eca {

constexpr int C = 384, HW = 384 * 384;
constexpr int G = 132;
constexpr int REP = 4;
constexpr int U = 4096;
constexpr int Q = 5;
constexpr int BLK = Q * U;
constexpr int NB = 11;
#define ECA_NRB 9
#define ECA_RINC 224
#define ECA_RDEC 56
constexpr int NRB = ECA_NRB;
constexpr int BPG = 14;
constexpr int NBLK = 3 * BPG;
constexpr int LAG = 2;
constexpr int MAXSTEP = 80;
constexpr int MID = Q / 2;
constexpr uint32_t TSTEP = G * 16 * 768;
constexpr int NLAST = HW / 16 - (BPG * Q - 1) * G;
constexpr uint32_t SCR_OFF = NB * BLK, SV_OFF = SCR_OFF + 4352, BAR_OFF = SV_OFF + 768, SMEM_BYTES = BAR_OFF + 128;
constexpr uint32_t BAR_PUB = BAR_OFF, BAR_S = BAR_OFF + 24, BAR_TMA = BAR_OFF + 56, BAR_STEP = BAR_OFF + 64;

struct Prog { int n; int stagger; int xd0; int xd1; uint4 e[MAXSTEP]; };

__device__ __align__(256) uint32_t g_part[48][G + 4][8];
__device__ __align__(256) uint32_t g_s[REP][256];
__device__ unsigned g_arrive;
#define ECA_STAMP(cond, idx) do { } while (0)

__device__ __forceinline__ uint32_t now_ns() { uint32_t t; asm volatile("mov.u32 %0, %globaltimer_lo;" : "=r"(t)); return t; }
__device__ __forceinline__ void mbar_init(uint32_t bar, uint32_t cnt) { asm volatile("mbarrier.init.shared::cta.b64 [%0], %1;" :: "r"(bar), "r"(cnt) : "memory"); }
__device__ __forceinline__ void mbar_arrive(uint32_t bar) { asm volatile("mbarrier.arrive.shared::cta.b64 _, [%0];" :: "r"(bar) : "memory"); }
__device__ __forceinline__ void mbar_wait(uint32_t bar, uint32_t parity) {
#pragma unroll 1
    for (int i = 0; i < (1 << 21); i++) {
        uint32_t ok;
        asm volatile("{\n.reg .pred p;\nmbarrier.try_wait.parity.shared::cta.b64 p, [%1], %2, 1000;\nselp.u32 %0, 1, 0, p;\n}"
                     : "=r"(ok) : "r"(bar), "r"(parity) : "memory");
        if (ok) return;
    }
}
__device__ __forceinline__ void spin_ns(uint32_t ns) {
    const uint32_t a = now_ns();
#pragma unroll 1
    for (int it = 0; it < 256; it++) { if (now_ns() - a >= ns) break; __nanosleep(32); }
}
__device__ __forceinline__ uint32_t opaque(uint32_t a) { uint32_t t; asm volatile("max.u32 %0, %1, 16;" : "=r"(t) : "r"(a)); return t; }
__device__ __forceinline__ uint64_t policy_evict_first() { uint64_t p; asm volatile("createpolicy.fractional.L2::evict_first.b64 %0, 1.0;" : "=l"(p)); return p; }
__device__ __forceinline__ uint4 lds128(uint32_t a) { uint4 v; asm volatile("ld.volatile.shared.v4.u32 {%0,%1,%2,%3}, [%4];" : "=r"(v.x), "=r"(v.y), "=r"(v.z), "=r"(v.w) : "r"(a) : "memory"); return v; }
__device__ __forceinline__ void sts128(uint32_t a, uint4 v) { asm volatile("st.shared.v4.u32 [%0], {%1,%2,%3,%4};" :: "r"(a), "r"(v.x), "r"(v.y), "r"(v.z), "r"(v.w) : "memory"); }
__device__ __forceinline__ void stg128(void* p, uint4 v, uint64_t pol) {
    asm volatile("st.global.L1::no_allocate.L2::cache_hint.v4.u32 [%0], {%1,%2,%3,%4}, %5;" :: "l"(p), "r"(v.x), "r"(v.y), "r"(v.z), "r"(v.w), "l"(pol) : "memory");
}
__device__ __forceinline__ void accum(float* a, uint4 v) {
    a[0] += __uint_as_float(v.x << 16); a[1] += __uint_as_float(v.x & 0xffff0000u);
    a[2] += __uint_as_float(v.y << 16); a[3] += __uint_as_float(v.y & 0xffff0000u);
    a[4] += __uint_as_float(v.z << 16); a[5] += __uint_as_float(v.z & 0xffff0000u);
    a[6] += __uint_as_float(v.w << 16); a[7] += __uint_as_float(v.w & 0xffff0000u);
}
__device__ __forceinline__ uint32_t bmul2(uint32_t a, uint32_t b) { uint32_t d; asm("mul.rn.bf16x2 %0, %1, %2;" : "=r"(d) : "r"(a), "r"(b)); return d; }
__device__ __forceinline__ uint4 scale(uint4 v, uint4 s) { return make_uint4(bmul2(v.x, s.x), bmul2(v.y, s.y), bmul2(v.z, s.z), bmul2(v.w, s.w)); }
__device__ __forceinline__ float bf16r(float x) { return __bfloat162float(__float2bfloat16_rn(x)); }
__device__ __forceinline__ __nv_bfloat16 gate(float sum, float n, float w) {
    const float g = bf16r(__fdiv_rn(bf16r(sum), n));
    const float z = bf16r(g * w);
    return __float2bfloat16_rn(__fdiv_rn(1.f, 1.f + expf(-z)));
}
__device__ __forceinline__ uint32_t enc(float v) { return ~min(__float_as_uint(v), 0xFFFFFFFEu); }

template <int LO, int HI> __device__ __forceinline__ void swap_block(uint4* r, int batch, uint32_t a) {
    if constexpr (HI - LO == 1) {
#pragma unroll
        for (int k = 0; k < Q; k++) { const uint4 t = lds128(a + k * U); sts128(a + k * U, r[LO * Q + k]); r[LO * Q + k] = t; }
    } else {
        if (batch < (LO + HI) / 2) swap_block<LO, (LO + HI) / 2>(r, batch, a); else swap_block<(LO + HI) / 2, HI>(r, batch, a);
    }
}
template <int K> __device__ __forceinline__ void load_block(uint32_t sa, const char* src, uint32_t lastsz, uint64_t pol) {
    if constexpr (K < Q - 1) {
        asm volatile("cp.async.cg.shared.global.L2::cache_hint [%0+%3], [%1+%4], 16, %2;"
                     :: "r"(sa), "l"(src), "l"(pol), "n"(K * U), "n"((K - MID) * (int)TSTEP) : "memory");
        load_block<K + 1>(sa, src, lastsz, pol);
    } else {
        asm volatile("cp.async.cg.shared.global.L2::cache_hint [%0+%4], [%1], 16, %3, %2;"
                     :: "r"(sa), "l"(src + (lastsz ? (K - MID) * (int)TSTEP : 0)), "l"(pol), "r"(lastsz), "n"(K * U) : "memory");
    }
}

__global__ void __launch_bounds__(384, 1)
eca_kernel(const char* __restrict__ x, const __nv_bfloat16* __restrict__ w1d, char* __restrict__ out, const __grid_constant__ Prog S) {
    extern __shared__ __align__(128) char smem[];
    const int tid = threadIdx.x, lane = tid & 31, warp = tid >> 5;
    const int b = blockIdx.x;
    const uint32_t s0 = (uint32_t)__cvta_generic_to_shared(smem);
    const uint32_t tstart = now_ns();
    const uint32_t sbase = opaque(s0 + tid * 16);
    const uint32_t gbase = opaque((b * 16 + warp * 2 + (lane >> 4)) * 768 + (lane & 15) * 16 + MID * TSTEP);
    const uint64_t pol = policy_evict_first();
    if (warp < 8) {
        load_block<0>(sbase, x + gbase, 16, pol);
        asm volatile("cp.async.commit_group;" ::: "memory");
    } else if (tid == 256) {
        for (int g = 0; g < 3; g++) mbar_init(s0 + BAR_PUB + g * 8, 8);
        for (int g = 0; g < 4; g++) mbar_init(s0 + BAR_S + g * 8, 1);
        mbar_init(s0 + BAR_TMA, 1); mbar_init(s0 + BAR_STEP, 8); mbar_init(s0 + BAR_STEP + 8, 8);
        asm volatile("fence.proxy.async.shared::cta;" ::: "memory");
    }
    __syncthreads();

    if (warp >= 8) {
        asm volatile("setmaxnreg.dec.sync.aligned.u32 %0;" :: "n"(ECA_RDEC));
        if (warp == 8) {
#pragma unroll
            for (int i = 0; i < 3; i++) *(uint4*)&g_part[i * 16 + (lane & 15)][b][(lane >> 4) * 4] = make_uint4(0, 0, 0, 0);
            if (b < REP) { *(uint4*)&g_s[b][lane * 4] = make_uint4(0, 0, 0, 0); *(uint4*)&g_s[b][128 + lane * 4] = make_uint4(0, 0, 0, 0); }
            __threadfence();
            __syncwarp();
            if (lane == 0) {
                const bool gen = atomicInc(&g_arrive, 2 * G - 1) >= G;
#pragma unroll 1
                for (int it = 0; it < (1 << 21); it++) {
                    unsigned v; asm volatile("ld.relaxed.gpu.global.u32 %0, [%1];" : "=r"(v) : "l"(&g_arrive) : "memory");
                    if ((v >= G) != gen) break;
                    __nanosleep(200);
                }
            }
            __syncwarp();
            __threadfence();
            const float wv = __bfloat162float(w1d[0]);
            uint32_t tph = 0;
#pragma unroll 1
            for (int rnd = -1; rnd < 3; rnd++) {
                const bool first = rnd < 0;
                const int g = first ? 0 : rnd;
                if (!first) mbar_wait(s0 + BAR_PUB + g * 8, 0);
                float k0 = 0.f, k1 = 0.f, k2 = 0.f, k3 = 0.f;
#pragma unroll 2
                for (int i = 0; i < 8; i++) {
                    const uint4 p = lds128(s0 + SCR_OFF + i * 512 + lane * 16);
                    k0 += __uint_as_float(p.x); k1 += __uint_as_float(p.y); k2 += __uint_as_float(p.z); k3 += __uint_as_float(p.w);
                }
                if (!first)
                    asm volatile("st.relaxed.gpu.global.v4.u32 [%0], {%1,%2,%3,%4};" :: "l"(&g_part[g * 16 + (lane & 15)][b][(lane >> 4) * 4]),
                                 "r"(enc(k0)), "r"(enc(k1)), "r"(enc(k2)), "r"(enc(k3)) : "memory");
                ECA_STAMP(lane == 0, 1 + 2 * g);
                if ((b & 7) == 0 && b < 128) {
                    const int cg = g * 16 + (b >> 3);
#pragma unroll 1
                    for (int it = 0; it < (1 << 20); it++) {
                        spin_ns(it ? 100 : S.xd0);
                        __syncwarp();
                        if (lane == 0) {
                            asm volatile("fence.proxy.async.shared::cta;" ::: "memory");
                            asm volatile("mbarrier.arrive.expect_tx.shared::cta.b64 _, [%0], %1;" :: "r"(s0 + BAR_TMA), "n"(G * 32) : "memory");
                            asm volatile("cp.async.bulk.shared::cluster.global.mbarrier::complete_tx::bytes [%0], [%1], %2, [%3];"
                                         :: "r"(s0 + SCR_OFF), "l"(&g_part[cg][0][0]), "n"(G * 32), "r"(s0 + BAR_TMA) : "memory");
                        }
                        mbar_wait(s0 + BAR_TMA, tph); tph ^= 1;
                        k0 = 0.f;
                        uint32_t mn = ~0u;
#pragma unroll 11
                        for (int i = 0; i < G / 4; i++) {
                            uint32_t p; asm volatile("ld.volatile.shared.u32 %0, [%1];" : "=r"(p) : "r"(s0 + SCR_OFF + lane * 4 + i * 128) : "memory");
                            mn = min(mn, p); k0 += __uint_as_float(~p);
                        }
                        if (__all_sync(0xffffffffu, mn != 0 || first)) break;
                    }
                    k0 += __shfl_xor_sync(0xffffffffu, k0, 8); k0 += __shfl_xor_sync(0xffffffffu, k0, 16);
                    const uint32_t hb = __bfloat16_as_ushort(gate(k0, (float)HW, wv)) & 0x7fffu;
                    const uint32_t w2 = ~(hb | (__shfl_xor_sync(0xffffffffu, hb, 1) << 16));
                    if (!(lane & 1) && !first)
                        asm volatile("st.relaxed.gpu.global.u32 [%0], %1;" :: "l"(&g_s[lane >> 3][cg * 4 + ((lane & 7) >> 1)]), "r"(w2) : "memory");
                } else {
                    spin_ns(S.xd1);
                }
                uint32_t a0, a1;
#pragma unroll 1
                for (int it = 0; it < (1 << 21); it++) {
                    asm volatile("ld.relaxed.gpu.global.v2.u32 {%0,%1}, [%2];" : "=r"(a0), "=r"(a1) : "l"(&g_s[b % REP][g * 64 + lane * 2]) : "memory");
                    if (__all_sync(0xffffffffu, (a0 && a1) || first)) break;
                    spin_ns(150);
                }
                asm volatile("st.shared.v2.u32 [%0], {%1,%2};" :: "r"(s0 + SV_OFF + g * 256 + lane * 8), "r"(~a0), "r"(~a1) : "memory");
                ECA_STAMP(lane == 0, 2 + 2 * g);
                __syncwarp();
                if (lane == 0) mbar_arrive(s0 + BAR_S + (rnd + 1) * 8);
            }
        }
    } else {
        asm volatile("setmaxnreg.inc.sync.aligned.u32 %0;" :: "n"(ECA_RINC));
        ECA_STAMP(tid == 0, 0);
        const uint32_t t0 = tstart + ((warp * 5 + b) & 7) * S.stagger;
        const bool hasLast = b < NLAST;
        float acc[8];
#pragma unroll
        for (int i = 0; i < 8; i++) acc[i] = 0.f;
        if (S.e[(lane % (MAXSTEP / 4)) * 4].z == 0xffffffffu) acc[0] = 1.f;
        uint4 r[NRB * Q];
#pragma unroll
        for (int i = 0; i < NRB * Q; i++) r[i] = make_uint4(0, 0, 0, 0);
        uint4 s4 = make_uint4(0, 0, 0, 0);
#pragma unroll 1
        for (int j = 1; j < S.n; j++) {
            const uint4 e = S.e[j];
            {
                const uint32_t tt = t0 + (e.w >> 12);
#pragma unroll 1
                for (int it = 0; it < 4096; it++) { const int d = (int)(tt - now_ns()); if (d <= 0) break; if (d > 100) __nanosleep(32); }
            }
            if (e.w & 4) {
                const int g = (e.w >> 8) & 3;
                mbar_wait(s0 + BAR_S + 8 + g * 8, 0);
                s4 = lds128(s0 + SV_OFF + g * 256 + (lane & 15) * 16);
            }
            if (j >= 3) mbar_wait(s0 + BAR_STEP + (j & 1) * 8, ((j - 3) >> 1) & 1);
            if (e.y & 1) {
                const uint32_t sa = sbase + ((e.z >> 8) & 15) * BLK;
                char* dst = out + (gbase + (e.y & ~127u));
                const bool full = hasLast || !(e.y & 4);
#pragma unroll
                for (int k = 0; k < Q; k++) {
                    const uint4 u = lds128(sa + k * U);
                    if (k < Q - 1 || full) stg128(dst + (k - MID) * (int)TSTEP, scale(u, s4), pol);
                }
            }
            if (e.x & 1) {
                const char* src = x + (gbase + (e.x & ~127u));
                const bool full = hasLast || !(e.x & 4);
                load_block<0>(opaque(sbase + (e.z & 15) * BLK), src, full ? 16 : 0, pol);
                if ((e.x & 2) && (lane & 7) == 0) {
#pragma unroll
                    for (int k = 0; k < Q; k++)
                        if (k < Q - 1 || full) asm volatile("prefetch.global.L2 [%0];" :: "l"(src + (k - MID) * (int)TSTEP) : "memory");
                }
            }
            asm volatile("cp.async.commit_group;" ::: "memory");
            asm volatile("cp.async.wait_group %0;" :: "n"(LAG) : "memory");
            if (e.z & (1u << 12)) {
                const uint32_t sa = sbase + ((e.z >> 4) & 15) * BLK;
#pragma unroll
                for (int k = 0; k < Q; k++) accum(acc, lds128(sa + k * U));
            }
            if (e.z & (1u << 13)) swap_block<0, NRB>(r, (e.z >> 20) & 15, sbase + ((e.z >> 16) & 15) * BLK);
            if (e.w & 1) {
                const int g = (e.w >> 4) & 3;
                const bool h = lane & 16;
                float k0 = h ? acc[4] : acc[0], k1 = h ? acc[5] : acc[1], k2 = h ? acc[6] : acc[2], k3 = h ? acc[7] : acc[3];
                k0 += __shfl_xor_sync(0xffffffffu, h ? acc[0] : acc[4], 16); k1 += __shfl_xor_sync(0xffffffffu, h ? acc[1] : acc[5], 16);
                k2 += __shfl_xor_sync(0xffffffffu, h ? acc[2] : acc[6], 16); k3 += __shfl_xor_sync(0xffffffffu, h ? acc[3] : acc[7], 16);
                mbar_wait(s0 + BAR_S + g * 8, 0);
                sts128(sbase + SCR_OFF, make_uint4(__float_as_uint(k0), __float_as_uint(k1), __float_as_uint(k2), __float_as_uint(k3)));
                __syncwarp();
                if (lane == 0) mbar_arrive(s0 + BAR_PUB + g * 8);
#pragma unroll
                for (int i = 0; i < 8; i++) acc[i] = 0.f;
            }
            __syncwarp();
            if (lane == 0) mbar_arrive(s0 + BAR_STEP + (j & 1) * 8);
        }
        ECA_STAMP(tid == 0, 14);
    }
}

struct Plan {
    int nL2;
    int dPoll;
    int nAbs;
    int absSteps;
    int tFirst, tL, tS1, tS2, tS3;
    int stagger, xd0, xd1;
};
static inline uint32_t enc_block(int t) { return (uint32_t)(t % BPG) * Q * TSTEP + (t / BPG) * 256 + 1 + ((t % BPG == BPG - 1) ? 4 : 0); }

static bool build_program(const Plan& P, Prog& prog) {
    memset(&prog, 0, sizeof(prog));
    prog.stagger = P.stagger; prog.xd0 = P.xd0; prog.xd1 = P.xd1;
    int blk[NB], ready[NB], kind[NB], reg[NRB], accAt[MAXSTEP + LAG + 1];
    for (int k = 0; k < NB; k++) { blk[k] = -1; ready[k] = 0; kind[k] = 0; }
    for (int k = 0; k < NRB; k++) reg[k] = -1;
    for (int k = 0; k < MAXSTEP + LAG + 1; k++) accAt[k] = -1;
    int pubAt[3] = {1 << 20, 1 << 20, 1 << 20}, remain[3] = {BPG, BPG, BPG};
    const int E = NBLK - NB - NRB - P.nL2;
    int li = 0, l2next = 0, stored = 0, sg = -1;
    double credit = 0.999, t = 0;
    int j = 0;
    for (;; j++) {
        if (j >= MAXSTEP) return false;
        uint4 e = {0, 0, 0, 0};
        const bool readsDone = li >= NBLK;
        int nfree = 0, fb = -1;
        if ((sg < 0 || remain[sg] == 0) && sg < 2 && j >= pubAt[sg + 1] + (sg < 0 ? P.dPoll : 1)) { sg++; e.w |= 4 | sg << 8; }
        if (sg == 2 && remain[2] == 0) break;
        for (int k = 0; k < NB; k++) nfree += blk[k] < 0;
        bool doit = readsDone;
        if (sg >= 0 && !readsDone && stored < E) {
            const int start = pubAt[0] + P.dPoll;
            credit += j < start + P.absSteps ? (double)P.nAbs / P.absSteps : 1.0;
            if (credit > 1.999) credit = 1.999;
            doit = credit >= 1.0 || nfree == 0;
        }
        if (doit && sg >= 0) {
            int best = -1;
            for (int k = 0; k < NB; k++)
                if (blk[k] >= 0 && blk[k] / BPG == sg && ready[k] < j && kind[k] != 1) {
                    if (best < 0 || (kind[k] == 2) > (kind[best] == 2) || ((kind[k] == 2) == (kind[best] == 2) && blk[k] < blk[best])) best = k;
                }
            if (best >= 0) { e.y = enc_block(blk[best]); e.z |= best << 8; blk[best] = -1; remain[sg]--; stored++; credit -= 1.0; }
        }
        for (int k = NB - 1; k >= 0; k--) if (blk[k] < 0) fb = k;
        if (!readsDone) {
            if (fb < 0) return false;
            const bool l2 = li >= BPG && li < BPG + P.nL2;
            e.x = enc_block(li) | (l2 ? 2 : 0); e.z |= fb;
            blk[fb] = li; ready[fb] = j + LAG; kind[fb] = l2; accAt[j + LAG] = fb;
            if (li % BPG == BPG - 1) pubAt[li / BPG] = j + LAG;
            li++;
        } else if (l2next < P.nL2 && fb >= 0) {
            e.x = enc_block(BPG + l2next); e.z |= fb;
            blk[fb] = BPG + l2next; ready[fb] = j + LAG; kind[fb] = 2;
            l2next++;
        }
        if (accAt[j] >= 0) { e.z |= accAt[j] << 4 | 1u << 12; if (kind[accAt[j]] == 1) blk[accAt[j]] = -1; }
        {
            int eb = -1, mb = -1, best = -1;
            nfree = 0; fb = -1;
            for (int i = NRB - 1; i >= 0; i--) { if (reg[i] < 0) eb = i; else if (mb < 0 || reg[i] < reg[mb]) mb = i; }
            for (int k = NB - 1; k >= 0; k--) {
                if (blk[k] < 0) { nfree++; fb = k; }
                else if (ready[k] <= j && kind[k] == 0 && (best < 0 || blk[k] > blk[best])) best = k;
            }
            int sb = -1, sk = -1;
            if (li < NBLK && nfree == 0 && eb >= 0 && best >= 0) { sb = eb; sk = best; }
            else if (mb >= 0 && best >= 0 && reg[mb] / BPG < blk[best] / BPG) { sb = mb; sk = best; }
            else if (li >= NBLK && l2next >= P.nL2 && mb >= 0 && fb >= 0) { sb = mb; sk = fb; }
            if (sb >= 0) { e.z |= 1u << 13 | sk << 16 | sb << 20; const int tmp = reg[sb]; reg[sb] = blk[sk]; blk[sk] = tmp; ready[sk] = j; kind[sk] = 0; }
        }
        for (int g = 0; g < 3; g++) if (j == pubAt[g]) e.w |= 1 | g << 4;
        e.w |= (uint32_t)t << 12;
        if (!readsDone) t += j == 0 ? P.tFirst : P.tL;
        if (e.y & 1) t += readsDone ? P.tS3 : (stored <= P.nAbs ? P.tS1 : P.tS2);
        prog.e[j] = e;
    }
    prog.n = j;
    return prog.e[0].x == enc_block(0) && prog.e[0].z == 0;
}

static const Plan kPlan = {4, 6, 9, 12, 600, 850, 250, 1200, 840, 100, 300, 1000};

constexpr int FB_BLOCKS = 256, FB_MAXC = 4096;
__device__ float g_fb_part[FB_BLOCKS * FB_MAXC / 8];
__device__ __nv_bfloat16 g_fb_s[FB_MAXC];
__global__ void fb_sum(const __nv_bfloat16* __restrict__ x, int rows) {
    for (int c = threadIdx.x; c < C; c += blockDim.x) {
        float a = 0.f;
        for (int r = blockIdx.x; r < rows; r += gridDim.x) a += __bfloat162float(x[(size_t)r * C + c]);
        g_fb_part[blockIdx.x * C + c] = a;
    }
}
__global__ void fb_gate(const __nv_bfloat16* __restrict__ w1d, int rows) {
    for (int c = threadIdx.x; c < C; c += blockDim.x) {
        float a = 0.f;
        for (int i = 0; i < FB_BLOCKS; i++) a += g_fb_part[i * C + c];
        g_fb_s[c] = gate(a, (float)rows, __bfloat162float(w1d[0]));
    }
}
__global__ void fb_scale(const __nv_bfloat16* __restrict__ x, __nv_bfloat16* __restrict__ out, size_t n) {
    for (size_t i = blockIdx.x * (size_t)blockDim.x + threadIdx.x; i < n; i += (size_t)gridDim.x * blockDim.x) out[i] = __hmul(x[i], g_fb_s[i % C]);
}

}

extern "C" void kernel_launch(void* const* d_in, const int* in_sizes, int n_in, void* d_out, int out_size) {
    using namespace eca;
    (void)n_in; (void)out_size;
    static int mode = -1;
    static Prog prog;
    if (mode < 0) {
        int dev = 0, sms = 0, occ = 0;
        cudaGetDevice(&dev);
        cudaDeviceGetAttribute(&sms, cudaDevAttrMultiProcessorCount, dev);
        bool ok = cudaFuncSetAttribute(eca_kernel, cudaFuncAttributeMaxDynamicSharedMemorySize, SMEM_BYTES) == cudaSuccess;
        ok = ok && cudaOccupancyMaxActiveBlocksPerMultiprocessor(&occ, eca_kernel, 384, SMEM_BYTES) == cudaSuccess;
        ok = ok && occ >= 1 && sms >= G && build_program(kPlan, prog);
        (void)cudaGetLastError();
        mode = ok ? 1 : 0;
    }
    const __nv_bfloat16* x = (const __nv_bfloat16*)d_in[0];
    const __nv_bfloat16* w = (const __nv_bfloat16*)d_in[1];
    const bool aligned = (((uintptr_t)x | (uintptr_t)d_out) & 15) == 0;
    if (mode == 1 && in_sizes[0] == HW * C && aligned) {
        eca_kernel<<<G, 384, SMEM_BYTES, cudaStreamPerThread>>>((const char*)x, w, (char*)d_out, prog);
    } else {
        const int rows = in_sizes[0] / C;
        fb_sum<<<FB_BLOCKS, 384, 0, cudaStreamPerThread>>>(x, rows);
        fb_gate<<<1, 384, 0, cudaStreamPerThread>>>(w, rows);
        fb_scale<<<1024, 256, 0, cudaStreamPerThread>>>(x, (__nv_bfloat16*)d_out, (size_t)in_sizes[0]);
    }
}
```

```cpp
#include <cuda_runtime.h>
#include <cuda_bf16.h>
#include <stdint.h>
#include <string.h>

namespace eca {

constexpr int C = 384, HW = 384 * 384;
constexpr int G = 132;
constexpr int REP = 4;
constexpr int U = 4096;
constexpr int Q = 5;
constexpr int BLK = Q * U;
constexpr int NB = 11;
#define ECA_NRB 10
#define ECA_RINC 240
#define ECA_RDEC 24
constexpr int NRB = ECA_NRB;
constexpr int BPG = 14;
constexpr int NBLK = 3 * BPG;
constexpr int LAG = 2;
constexpr int MAXSTEP = 80;
constexpr int MID = Q / 2;
constexpr uint32_t TSTEP = G * 16 * 768;
constexpr int NLAST = HW / 16 - (BPG * Q - 1) * G;
constexpr uint32_t SCR_OFF = NB * BLK, SV_OFF = SCR_OFF + 4352, BAR_OFF = SV_OFF + 768, SMEM_USED = BAR_OFF + 128;
constexpr uint32_t SMEM_BYTES = SMEM_USED;
constexpr uint32_t BAR_PUB = BAR_OFF, BAR_S = BAR_OFF + 24, BAR_TMA = BAR_OFF + 56, BAR_STEP = BAR_OFF + 64, W_OFF = BAR_OFF + 96;

struct Prog { int n; int stagger; int xd0; int xd1; uint4 e[MAXSTEP]; };

__device__ __align__(256) uint32_t g_part[48][G + 4][8];
__device__ __align__(256) uint32_t g_s[REP][256];
__device__ unsigned g_arrive;
#define ECA_PUT(cond, idx, val) do { } while (0)
#define ECA_STAMP(cond, idx) ECA_PUT(cond, idx, now_ns())

__device__ __forceinline__ uint32_t now_ns() { uint32_t t; asm volatile("mov.u32 %0, %globaltimer_lo;" : "=r"(t)); return t; }
__device__ __forceinline__ void mbar_init(uint32_t bar, uint32_t cnt) { asm volatile("mbarrier.init.shared::cta.b64 [%0], %1;" :: "r"(bar), "r"(cnt) : "memory"); }
__device__ __forceinline__ void mbar_arrive(uint32_t bar) { asm volatile("mbarrier.arrive.shared::cta.b64 _, [%0];" :: "r"(bar) : "memory"); }
__device__ __forceinline__ void mbar_wait(uint32_t bar, uint32_t parity) {
#pragma unroll 1
    for (int i = 0; i < (1 << 21); i++) {
        uint32_t ok;
        asm volatile("{\n.reg .pred p;\nmbarrier.try_wait.parity.shared::cta.b64 p, [%1], %2, 1000;\nselp.u32 %0, 1, 0, p;\n}"
                     : "=r"(ok) : "r"(bar), "r"(parity) : "memory");
        if (ok) return;
    }
}
__device__ __forceinline__ void spin_ns(uint32_t ns) {
    const uint32_t a = now_ns();
#pragma unroll 1
    for (int it = 0; it < 256; it++) { if (now_ns() - a >= ns) break; __nanosleep(32); }
}
__device__ __forceinline__ uint32_t opaque(uint32_t a) { uint32_t t; asm volatile("max.u32 %0, %1, 16;" : "=r"(t) : "r"(a)); return t; }
__device__ __forceinline__ uint64_t policy_evict_first() { uint64_t p; asm volatile("createpolicy.fractional.L2::evict_first.b64 %0, 1.0;" : "=l"(p)); return p; }
__device__ __forceinline__ uint4 lds128(uint32_t a) { uint4 v; asm volatile("ld.volatile.shared.v4.u32 {%0,%1,%2,%3}, [%4];" : "=r"(v.x), "=r"(v.y), "=r"(v.z), "=r"(v.w) : "r"(a) : "memory"); return v; }
__device__ __forceinline__ void sts128(uint32_t a, uint4 v) { asm volatile("st.volatile.shared.v4.u32 [%0], {%1,%2,%3,%4};" :: "r"(a), "r"(v.x), "r"(v.y), "r"(v.z), "r"(v.w) : "memory"); }
__device__ __forceinline__ void stg128(void* p, uint4 v, uint64_t pol) {
    asm volatile("st.global.L1::no_allocate.L2::cache_hint.v4.u32 [%0], {%1,%2,%3,%4}, %5;" :: "l"(p), "r"(v.x), "r"(v.y), "r"(v.z), "r"(v.w), "l"(pol) : "memory");
}
__device__ __forceinline__ void accum(float* a, uint4 v) {
    a[0] += __uint_as_float(v.x << 16); a[1] += __uint_as_float(v.x & 0xffff0000u);
    a[2] += __uint_as_float(v.y << 16); a[3] += __uint_as_float(v.y & 0xffff0000u);
    a[4] += __uint_as_float(v.z << 16); a[5] += __uint_as_float(v.z & 0xffff0000u);
    a[6] += __uint_as_float(v.w << 16); a[7] += __uint_as_float(v.w & 0xffff0000u);
}
__device__ __forceinline__ uint32_t bmul2(uint32_t a, uint32_t b) { uint32_t d; asm("mul.rn.bf16x2 %0, %1, %2;" : "=r"(d) : "r"(a), "r"(b)); return d; }
__device__ __forceinline__ uint4 scale(uint4 v, uint4 s) { return make_uint4(bmul2(v.x, s.x), bmul2(v.y, s.y), bmul2(v.z, s.z), bmul2(v.w, s.w)); }
__device__ __forceinline__ float bf16r(float x) { return __bfloat162float(__float2bfloat16_rn(x)); }
__device__ __forceinline__ __nv_bfloat16 gate(float sum, float n, float w) {
    const float g = bf16r(__fdiv_rn(bf16r(sum), n));
    const float z = bf16r(g * w);
    return __float2bfloat16_rn(__fdiv_rn(1.f, 1.f + expf(-z)));
}
__device__ __forceinline__ uint32_t enc(float v) { return ~min(__float_as_uint(v), 0xFFFFFFFEu); }

template <int LO, int HI> __device__ __forceinline__ void swap_block(uint4* r, int sel, uint32_t a) {
    if constexpr (HI - LO == 1) {
        uint4* v = r + (LO >> 1) * Q;
        const uint4 t = lds128(a);
        if constexpr ((LO & 1) == 0) {
#pragma unroll
            for (int k = 0; k < Q - 1; k++) { sts128(a + k * U, v[k]); v[k] = lds128(a + (k + 1) * U); }
            sts128(a + (Q - 1) * U, v[Q - 1]); v[Q - 1] = t;
        } else {
#pragma unroll
            for (int k = Q - 1; k > 0; k--) { sts128(a + ((k + 1) % Q) * U, v[k]); v[k] = lds128(a + k * U); }
            sts128(a + U, v[0]); v[0] = t;
        }
    } else {
        if (sel < (LO + HI) / 2) swap_block<LO, (LO + HI) / 2>(r, sel, a); else swap_block<(LO + HI) / 2, HI>(r, sel, a);
    }
}
template <int K> __device__ __forceinline__ void load_block(uint32_t sa, const char* src, uint32_t lastsz, uint64_t pol) {
    if constexpr (K < Q - 1) {
        asm volatile("cp.async.cg.shared.global.L2::cache_hint [%0+%3], [%1+%4], 16, %2;"
                     :: "r"(sa), "l"(src), "l"(pol), "n"(K * U), "n"((K - MID) * (int)TSTEP) : "memory");
        load_block<K + 1>(sa, src, lastsz, pol);
    } else {
        asm volatile("cp.async.cg.shared.global.L2::cache_hint [%0+%4], [%1], 16, %3, %2;"
                     :: "r"(sa), "l"(src + (lastsz ? (K - MID) * (int)TSTEP : 0)), "l"(pol), "r"(lastsz), "n"(K * U) : "memory");
    }
}

__global__ void __launch_bounds__(384, 1)
eca_kernel(const char* __restrict__ x, const __nv_bfloat16* __restrict__ w1d, char* __restrict__ out, const __grid_constant__ Prog S) {
    extern __shared__ __align__(1024) char smem[];
    const int tid = threadIdx.x, lane = tid & 31, warp = tid >> 5;
    const int b = blockIdx.x;
    const uint32_t s0 = (uint32_t)__cvta_generic_to_shared(smem);
    const uint32_t tstart = now_ns();
    const uint64_t pol = policy_evict_first();
    if (warp < 8) {
        load_block<0>(opaque(s0 + tid * 16), x + ((b * 16 + (tid >> 4)) * 768 + (tid & 15) * 16 + MID * TSTEP), 16, pol);
        asm volatile("cp.async.commit_group;" ::: "memory");
    } else if (tid == 256) {
        for (int g = 0; g < 3; g++) mbar_init(s0 + BAR_PUB + g * 8, 8);
        for (int g = 0; g < 4; g++) mbar_init(s0 + BAR_S + g * 8, 1);
        mbar_init(s0 + BAR_TMA, 1); mbar_init(s0 + BAR_STEP, 8); mbar_init(s0 + BAR_STEP + 8, 8);
        asm volatile("fence.proxy.async.shared::cta;" ::: "memory");
    }
    __syncthreads();

    if (warp >= 8) {
        asm volatile("setmaxnreg.dec.sync.aligned.u32 %0;" :: "n"(ECA_RDEC));
        if (warp == 8) {
#pragma unroll
            for (int i = 0; i < 3; i++) *(uint4*)&g_part[i * 16 + (lane & 15)][b][(lane >> 4) * 4] = make_uint4(0, 0, 0, 0);
            if (b < REP) { *(uint4*)&g_s[b][lane * 4] = make_uint4(0, 0, 0, 0); *(uint4*)&g_s[b][128 + lane * 4] = make_uint4(0, 0, 0, 0); }
            __threadfence();
            __syncwarp();
            if (lane == 0) {
                const bool gen = atomicInc(&g_arrive, 2 * G - 1) >= G;
#pragma unroll 1
                for (int it = 0; it < (1 << 21); it++) {
                    unsigned v; asm volatile("ld.relaxed.gpu.global.u32 %0, [%1];" : "=r"(v) : "l"(&g_arrive) : "memory");
                    if ((v >= G) != gen) break;
                    __nanosleep(200);
                }
            }
            __syncwarp();
            __threadfence();
            asm volatile("st.volatile.shared.f32 [%0], %1;" :: "r"(s0 + W_OFF), "f"(__bfloat162float(w1d[0])) : "memory");
            uint32_t tph = 0;
#pragma unroll 1
            for (int rnd = -1; rnd < 3; rnd++) {
                const bool first = rnd < 0;
                const int g = first ? 0 : rnd;
                if (!first) mbar_wait(s0 + BAR_PUB + g * 8, 0);
                float k0 = 0.f, k1 = 0.f, k2 = 0.f, k3 = 0.f;
#pragma unroll 2
                for (int i = 0; i < 8; i++) {
                    const uint4 p = lds128(s0 + SCR_OFF + i * 512 + lane * 16);
                    k0 += __uint_as_float(p.x); k1 += __uint_as_float(p.y); k2 += __uint_as_float(p.z); k3 += __uint_as_float(p.w);
                }
                if (!first)
                    asm volatile("st.relaxed.gpu.global.v4.u32 [%0], {%1,%2,%3,%4};" :: "l"(&g_part[g * 16 + (lane & 15)][b][(lane >> 4) * 4]),
                                 "r"(enc(k0)), "r"(enc(k1)), "r"(enc(k2)), "r"(enc(k3)) : "memory");
                ECA_STAMP(lane == 0, 1 + 2 * g);
                if ((b & 7) == 0 && b < 128) {
                    const int cg = g * 16 + (b >> 3);
#pragma unroll 1
                    for (int it = 0; it < (1 << 20); it++) {
                        spin_ns(it ? 100 : S.xd0);
                        __syncwarp();
                        if (lane == 0) {
                            asm volatile("fence.proxy.async.shared::cta;" ::: "memory");
                            asm volatile("mbarrier.arrive.expect_tx.shared::cta.b64 _, [%0], %1;" :: "r"(s0 + BAR_TMA), "n"(G * 32) : "memory");
                            asm volatile("cp.async.bulk.shared::cluster.global.mbarrier::complete_tx::bytes [%0], [%1], %2, [%3];"
                                         :: "r"(s0 + SCR_OFF), "l"(&g_part[cg][0][0]), "n"(G * 32), "r"(s0 + BAR_TMA) : "memory");
                        }
                        mbar_wait(s0 + BAR_TMA, tph); tph ^= 1;
                        k0 = 0.f;
                        uint32_t mn = ~0u;
#pragma unroll 11
                        for (int i = 0; i < G / 4; i++) {
                            uint32_t p; asm volatile("ld.volatile.shared.u32 %0, [%1];" : "=r"(p) : "r"(s0 + SCR_OFF + lane * 4 + i * 128) : "memory");
                            mn = min(mn, p); k0 += __uint_as_float(~p);
                        }
                        if (__all_sync(0xffffffffu, mn != 0 || first)) break;
                    }
                    k0 += __shfl_xor_sync(0xffffffffu, k0, 8); k0 += __shfl_xor_sync(0xffffffffu, k0, 16);
                    float wv; asm volatile("ld.volatile.shared.f32 %0, [%1];" : "=f"(wv) : "r"(s0 + W_OFF) : "memory");
                    const uint32_t hb = __bfloat16_as_ushort(gate(k0, (float)HW, wv)) & 0x7fffu;
                    const uint32_t w2 = ~(hb | (__shfl_xor_sync(0xffffffffu, hb, 1) << 16));
                    if (!(lane & 1) && !first)
                        asm volatile("st.relaxed.gpu.global.u32 [%0], %1;" :: "l"(&g_s[lane >> 3][cg * 4 + ((lane & 7) >> 1)]), "r"(w2) : "memory");
                } else {
                    spin_ns(S.xd1);
                }
                uint32_t a0, a1;
#pragma unroll 1
                for (int it = 0; it < (1 << 21); it++) {
                    asm volatile("ld.relaxed.gpu.global.v2.u32 {%0,%1}, [%2];" : "=r"(a0), "=r"(a1) : "l"(&g_s[b % REP][g * 64 + lane * 2]) : "memory");
                    if (__all_sync(0xffffffffu, (a0 && a1) || first)) break;
                    spin_ns(150);
                }
                asm volatile("st.shared.v2.u32 [%0], {%1,%2};" :: "r"(s0 + SV_OFF + g * 256 + lane * 8), "r"(~a0), "r"(~a1) : "memory");
                ECA_STAMP(lane == 0, 2 + 2 * g);
                __syncwarp();
                if (lane == 0) mbar_arrive(s0 + BAR_S + (rnd + 1) * 8);
            }
        }
    } else {
        asm volatile("setmaxnreg.inc.sync.aligned.u32 %0;" :: "n"(ECA_RINC));
        ECA_PUT(tid == 0, 0, tstart);
        const uint32_t sbase = __shfl_sync(0xffffffffu, s0 + tid * 16, lane);
        auto fresh = [&]() { uint32_t o; asm volatile("mov.u32 %0, %1;" : "=r"(o) : "r"(sbase)); return o; };
        const uint32_t gcta = b * (16 * 768) + MID * TSTEP - 3 * s0;
        auto gaddr = [&](uint32_t off) { const uint32_t o = fresh(); return o + (o >> 8) * 512 + gcta + (off & ~127u); };
        const bool hasLast = b < NLAST;
        float acc[8];
#pragma unroll
        for (int i = 0; i < 8; i++) acc[i] = 0.f;
        if (S.e[(lane % (MAXSTEP / 4)) * 4].z == 0xffffffffu) acc[0] = 1.f;
        uint4 r[NRB * Q];
#pragma unroll
        for (int i = 0; i < NRB * Q; i++) asm volatile("" : "=r"(r[i].x), "=r"(r[i].y), "=r"(r[i].z), "=r"(r[i].w));
        uint4 s4 = make_uint4(0, 0, 0, 0);
#pragma unroll 1
        for (int j = 1; j < S.n; j++) {
            const uint4 e = S.e[j];
            {
                const uint32_t tt = tstart + (((fresh() >> 9) * 5 + b) & 7) * S.stagger + (e.w >> 12);
#pragma unroll 1
                for (int it = 0; it < 4096; it++) { const int d = (int)(tt - now_ns()); if (d <= 0) break; if (d > 100) __nanosleep(32); }
            }
            if (e.w & 4) {
                const int g = (e.w >> 8) & 3;
                ECA_STAMP((sbase & 4095) == 1024, 8 + 2 * g);
                mbar_wait(s0 + BAR_S + 8 + g * 8, 0);
                ECA_STAMP((sbase & 4095) == 1024, 9 + 2 * g);
                s4 = lds128(s0 + SV_OFF + g * 256 + (sbase & 255));
            }
            ECA_STAMP((sbase & 4095) == 1024, 16 + j);
            if (j >= 3) mbar_wait(s0 + BAR_STEP + (j & 1) * 8, ((j - 3) >> 1) & 1);
            if (e.y & 1) {
                const uint32_t sa = sbase + ((e.z >> 8) & 15) * BLK;
                char* dst = out + gaddr(e.y);
                const bool full = hasLast || !(e.y & 4);
#pragma unroll
                for (int k = 0; k < Q; k++) {
                    const uint4 u = lds128(sa + k * U);
                    if (k < Q - 1 || full) stg128(dst + (k - MID) * (int)TSTEP, scale(u, s4), pol);
                }
            }
            if (e.x & 1) {
                const char* src = x + gaddr(e.x);
                const bool full = hasLast || !(e.x & 4);
                load_block<0>(opaque(sbase + (e.z & 15) * BLK), src, full ? 16 : 0, pol);
                if ((e.x & 2) && (sbase & 127) == 0) {
#pragma unroll
                    for (int k = 0; k < Q; k++)
                        if (k < Q - 1 || full) asm volatile("prefetch.global.L2 [%0];" :: "l"(src + (k - MID) * (int)TSTEP) : "memory");
                }
            }
            asm volatile("cp.async.commit_group;" ::: "memory");
            asm volatile("cp.async.wait_group %0;" :: "n"(LAG) : "memory");
            if (e.z & (1u << 12)) {
                const uint32_t sa = sbase + ((e.z >> 4) & 15) * BLK;
#pragma unroll
                for (int k = 0; k < Q; k++) accum(acc, lds128(sa + k * U));
            }
            if (e.z & (1u << 13)) swap_block<0, 2 * NRB>(r, e.z >> 20, sbase + ((e.z >> 16) & 15) * BLK);
            if (e.w & 1) {
                const int g = (e.w >> 4) & 3;
                const bool h = sbase & 256;
                float k0 = h ? acc[4] : acc[0], k1 = h ? acc[5] : acc[1], k2 = h ? acc[6] : acc[2], k3 = h ? acc[7] : acc[3];
                k0 += __shfl_xor_sync(0xffffffffu, h ? acc[0] : acc[4], 16); k1 += __shfl_xor_sync(0xffffffffu, h ? acc[1] : acc[5], 16);
                k2 += __shfl_xor_sync(0xffffffffu, h ? acc[2] : acc[6], 16); k3 += __shfl_xor_sync(0xffffffffu, h ? acc[3] : acc[7], 16);
                mbar_wait(s0 + BAR_S + g * 8, 0);
                sts128(sbase + SCR_OFF, make_uint4(__float_as_uint(k0), __float_as_uint(k1), __float_as_uint(k2), __float_as_uint(k3)));
                __syncwarp();
                if ((sbase & 511) == 0) mbar_arrive(s0 + BAR_PUB + g * 8);
#pragma unroll
                for (int i = 0; i < 8; i++) acc[i] = 0.f;
            }
            __syncwarp();
            if ((sbase & 511) == 0) mbar_arrive(s0 + BAR_STEP + (j & 1) * 8);
        }
    }
}

struct Plan {
    int nL2;
    int dPoll;
    int nAbs;
    int absSteps;
    int tFirst, tL;
    int tS1, tS2, n1, n2;
    int tF1, tF2, nF;
    int tE, nE;
    int stagger, xd0, xd1;
};
static inline uint32_t enc_block(int t) { return (uint32_t)(t % BPG) * Q * TSTEP + (t / BPG) * 256 + 1 + ((t % BPG == BPG - 1) ? 4 : 0); }

static bool build_program(const Plan& P, Prog& prog) {
    memset(&prog, 0, sizeof(prog));
    prog.stagger = P.stagger; prog.xd0 = P.xd0; prog.xd1 = P.xd1;
    int blk[NB], ready[NB], kind[NB], reg[NRB], par[NRB], accAt[MAXSTEP + LAG + 1];
    for (int k = 0; k < NB; k++) { blk[k] = -1; ready[k] = 0; kind[k] = 0; }
    for (int k = 0; k < NRB; k++) { reg[k] = -1; par[k] = 0; }
    for (int k = 0; k < MAXSTEP + LAG + 1; k++) accAt[k] = -1;
    int pubAt[3] = {1 << 20, 1 << 20, 1 << 20}, remain[3] = {BPG, BPG, BPG};
    const int E = NBLK - NB - NRB - P.nL2;
    int li = 0, l2next = 0, stored = 0, sg = -1;
    double credit = 0.999, t = 0;
    int j = 0;
    for (;; j++) {
        if (j >= MAXSTEP) return false;
        uint4 e = {0, 0, 0, 0};
        const bool readsDone = li >= NBLK;
        int nfree = 0, fb = -1;
        if ((sg < 0 || remain[sg] == 0) && sg < 2 && j >= pubAt[sg + 1] + (sg < 0 ? P.dPoll : 1)) { sg++; e.w |= 4 | sg << 8; }
        if (sg == 2 && remain[2] == 0) break;
        for (int k = 0; k < NB; k++) nfree += blk[k] < 0;
        bool doit = readsDone;
        if (sg >= 0 && !readsDone && stored < E) {
            const int start = pubAt[0] + P.dPoll;
            credit += j < start + P.absSteps ? (double)P.nAbs / P.absSteps : 1.0;
            if (credit > 1.999) credit = 1.999;
            doit = credit >= 1.0 || nfree == 0;
        }
        if (doit && sg >= 0) {
            int best = -1;
            for (int k = 0; k < NB; k++)
                if (blk[k] >= 0 && blk[k] / BPG == sg && ready[k] < j && kind[k] != 1) {
                    if (best < 0 || (kind[k] == 2) > (kind[best] == 2) || ((kind[k] == 2) == (kind[best] == 2) && blk[k] < blk[best])) best = k;
                }
            if (best >= 0) { e.y = enc_block(blk[best]); e.z |= best << 8; blk[best] = -1; remain[sg]--; stored++; credit -= 1.0; }
        }
        for (int k = NB - 1; k >= 0; k--) if (blk[k] < 0) fb = k;
        if (!readsDone) {
            if (fb < 0) return false;
            const bool l2 = li >= BPG && li < BPG + P.nL2;
            e.x = enc_block(li) | (l2 ? 2 : 0); e.z |= fb;
            blk[fb] = li; ready[fb] = j + LAG; kind[fb] = l2; accAt[j + LAG] = fb;
            if (li % BPG == BPG - 1) pubAt[li / BPG] = j + LAG;
            li++;
        } else if (l2next < P.nL2 && fb >= 0) {
            e.x = enc_block(BPG + l2next); e.z |= fb;
            blk[fb] = BPG + l2next; ready[fb] = j + LAG; kind[fb] = 2;
            l2next++;
        }
        if (accAt[j] >= 0) { e.z |= accAt[j] << 4 | 1u << 12; if (kind[accAt[j]] == 1) blk[accAt[j]] = -1; }
        {
            int eb = -1, mb = -1, best = -1;
            nfree = 0; fb = -1;
            for (int i = NRB - 1; i >= 0; i--) { if (reg[i] < 0) eb = i; else if (mb < 0 || reg[i] < reg[mb]) mb = i; }
            for (int k = NB - 1; k >= 0; k--) {
                if (blk[k] < 0) { nfree++; fb = k; }
                else if (ready[k] <= j && kind[k] == 0 && (best < 0 || blk[k] > blk[best])) best = k;
            }
            int sb = -1, sk = -1;
            if (li < NBLK && nfree == 0 && eb >= 0 && best >= 0) { sb = eb; sk = best; }
            else if (mb >= 0 && best >= 0 && reg[mb] / BPG < blk[best] / BPG) { sb = mb; sk = best; }
            else if (li >= NBLK && l2next >= P.nL2 && mb >= 0 && fb >= 0) { sb = mb; sk = fb; }
            if (sb >= 0) { e.z |= 1u << 13 | sk << 16 | (sb * 2 + par[sb]) << 20; par[sb] ^= 1; const int tmp = reg[sb]; reg[sb] = blk[sk]; blk[sk] = tmp; ready[sk] = j; kind[sk] = 0; }
        }
        for (int g = 0; g < 3; g++) if (j == pubAt[g]) e.w |= 1 | g << 4;
        e.w |= (uint32_t)t << 12;
        if (!readsDone) t += j == 0 ? P.tFirst : P.tL;
        if (e.y & 1) {
            const double f = readsDone ? (stored - E - 1) / (double)P.nF : (stored - P.n1) / (double)(P.n2 - P.n1);
            const double c = f < 0 ? 0 : f > 1 ? 1 : f;
            t += stored >= NBLK - P.nE ? P.tE : readsDone ? P.tF1 + c * (P.tF2 - P.tF1) : P.tS1 + c * (P.tS2 - P.tS1);
        }
        prog.e[j] = e;
    }
    prog.n = j;
    return prog.e[0].x == enc_block(0) && prog.e[0].z == 0;
}

static const Plan kPlan = {4, 6, 7, 13, 766, 847, 127, 1262, 3, 16, 1016, 794, 11, 836, 6, 110, 899, 2814};

constexpr int FB_BLOCKS = 256, FB_MAXC = 4096;
__device__ float g_fb_part[FB_BLOCKS * FB_MAXC / 8];
__device__ __nv_bfloat16 g_fb_s[FB_MAXC];
__global__ void fb_sum(const __nv_bfloat16* __restrict__ x, int rows) {
    for (int c = threadIdx.x; c < C; c += blockDim.x) {
        float a = 0.f;
        for (int r = blockIdx.x; r < rows; r += gridDim.x) a += __bfloat162float(x[(size_t)r * C + c]);
        g_fb_part[blockIdx.x * C + c] = a;
    }
}
__global__ void fb_gate(const __nv_bfloat16* __restrict__ w1d, int rows) {
    for (int c = threadIdx.x; c < C; c += blockDim.x) {
        float a = 0.f;
        for (int i = 0; i < FB_BLOCKS; i++) a += g_fb_part[i * C + c];
        g_fb_s[c] = gate(a, (float)rows, __bfloat162float(w1d[0]));
    }
}
__global__ void fb_scale(const __nv_bfloat16* __restrict__ x, __nv_bfloat16* __restrict__ out, size_t n) {
    for (size_t i = blockIdx.x * (size_t)blockDim.x + threadIdx.x; i < n; i += (size_t)gridDim.x * blockDim.x) out[i] = __hmul(x[i], g_fb_s[i % C]);
}

}

extern "C" void kernel_launch(void* const* d_in, const int* in_sizes, int n_in, void* d_out, int out_size) {
    using namespace eca;
    (void)n_in; (void)out_size;
    static int mode = -1;
    static Prog prog;
    if (mode < 0) {
        int dev = 0, sms = 0, occ = 0;
        cudaGetDevice(&dev);
        cudaDeviceGetAttribute(&sms, cudaDevAttrMultiProcessorCount, dev);
        bool ok = cudaFuncSetAttribute(eca_kernel, cudaFuncAttributeMaxDynamicSharedMemorySize, SMEM_BYTES) == cudaSuccess;
        ok = ok && cudaOccupancyMaxActiveBlocksPerMultiprocessor(&occ, eca_kernel, 384, SMEM_BYTES) == cudaSuccess;
        ok = ok && occ >= 1 && sms >= G && build_program(kPlan, prog);
        (void)cudaGetLastError();
        mode = ok ? 1 : 0;
    }
    const __nv_bfloat16* x = (const __nv_bfloat16*)d_in[0];
    const __nv_bfloat16* w = (const __nv_bfloat16*)d_in[1];
    const bool aligned = (((uintptr_t)x | (uintptr_t)d_out) & 15) == 0;
    if (mode == 1 && in_sizes[0] == HW * C && aligned) {
        eca_kernel<<<G, 384, SMEM_BYTES, cudaStreamPerThread>>>((const char*)x, w, (char*)d_out, prog);
    } else {
        const int rows = in_sizes[0] / C;
        fb_sum<<<FB_BLOCKS, 384, 0, cudaStreamPerThread>>>(x, rows);
        fb_gate<<<1, 384, 0, cudaStreamPerThread>>>(w, rows);
        fb_scale<<<1024, 256, 0, cudaStreamPerThread>>>(x, (__nv_bfloat16*)d_out, (size_t)in_sizes[0]);
    }
}
```

```cpp
#include <cuda_runtime.h>
#include <cuda_bf16.h>
#include <stdint.h>
#include <string.h>

namespace eca {

constexpr int C = 384, HW = 384 * 384;
constexpr int G = 132;
constexpr int REP = 4;
constexpr int U = 4096;
constexpr int Q = 5;
constexpr int BLK = Q * U;
constexpr int NB = 11;
#define ECA_NRB 10
#define ECA_RINC 240
#define ECA_RDEC 24
constexpr int NRB = ECA_NRB;
constexpr int BPG = 14;
constexpr int NBLK = 3 * BPG;
#define ECA_LAG 2
constexpr int LAG = ECA_LAG;
constexpr int MAXSTEP = 84;
#define ECA_MAP 2
constexpr uint32_t WSTEP = ECA_MAP == 0 ? 2 * 768 : ECA_MAP == 1 ? 2 * Q * 768 : G * 2 * Q * 768;
constexpr uint32_t CSTEP = ECA_MAP == 0 ? 16 * 768 : ECA_MAP == 1 ? 16 * Q * 768 : ECA_MAP == 2 ? 2 * 768 : 2 * Q * 768;
constexpr uint32_t KSTEP = ECA_MAP == 0 ? G * 16 * 768 : ECA_MAP == 2 ? G * 2 * 768 : 2 * 768;
constexpr uint32_t BSTEP = G * 16 * Q * 768;
constexpr uint32_t NBYTES = (uint32_t)HW * C * 2;
constexpr uint32_t SCR_OFF = NB * BLK, RED_OFF = SCR_OFF + 4096, SV_OFF = RED_OFF + 128, BAR_OFF = SV_OFF + 768, SMEM_USED = BAR_OFF + 128;
constexpr uint32_t SMEM_BYTES = SMEM_USED;
constexpr uint32_t BAR_PUB = BAR_OFF, BAR_DONE = BAR_PUB + 24, BAR_S = BAR_OFF + 32, BAR_STEP = BAR_OFF + 64, W_OFF = BAR_OFF + 96, LATE_OFF = BAR_OFF + 100, SHIFT_OFF = BAR_OFF + 112;

struct __align__(16) Step { uint32_t t, y, x, z; };
struct Prog { int n, stagger, xd0, xd1, xd2, xd3, theta, gain, tau, pad0, pad1, pad2; Step e[MAXSTEP]; uint32_t st[48]; };

constexpr uint32_t PROW = (G + 4) * 8;
__device__ __align__(256) uint32_t g_part[48 * PROW];
__device__ __align__(256) uint32_t g_s[REP * 256];
__device__ __align__(256) unsigned g_shift[4];
__device__ __align__(256) unsigned g_arrive;
#define ECA_PUT(cond, idx, val) do { } while (0)
#define ECA_STAMP(cond, idx) ECA_PUT(cond, idx, now_ns())

__device__ __forceinline__ uint32_t now_ns() { uint32_t t; asm volatile("mov.u32 %0, %globaltimer_lo;" : "=r"(t)); return t; }
__device__ __forceinline__ void mbar_init(uint32_t bar, uint32_t cnt) { asm volatile("mbarrier.init.shared::cta.b64 [%0], %1;" :: "r"(bar), "r"(cnt) : "memory"); }
__device__ __forceinline__ void mbar_arrive(uint32_t bar) { asm volatile("mbarrier.arrive.shared::cta.b64 _, [%0];" :: "r"(bar) : "memory"); }
__device__ __forceinline__ void mbar_wait(uint32_t bar, uint32_t parity) {
#pragma unroll 1
    for (int i = 0; i < (1 << 21); i++) {
        uint32_t ok;
        asm volatile("{\n.reg .pred p;\nmbarrier.try_wait.parity.shared::cta.b64 p, [%1], %2, 1000;\nselp.u32 %0, 1, 0, p;\n}"
                     : "=r"(ok) : "r"(bar), "r"(parity) : "memory");
        if (ok) return;
    }
}
__device__ __forceinline__ bool mbar_test(uint32_t bar) {
    uint32_t ok;
    asm volatile("{\n.reg .pred p;\nmbarrier.test_wait.parity.shared::cta.b64 p, [%1], 0;\nselp.u32 %0, 1, 0, p;\n}" : "=r"(ok) : "r"(bar) : "memory");
    return ok;
}
__device__ __forceinline__ void spin_ns(uint32_t ns) {
    const uint32_t a = now_ns();
#pragma unroll 1
    for (int it = 0; it < 256; it++) { if (now_ns() - a >= ns) break; __nanosleep(32); }
}
__device__ __forceinline__ uint32_t opaque(uint32_t a) { uint32_t t; asm volatile("max.u32 %0, %1, 16;" : "=r"(t) : "r"(a)); return t; }
__device__ __forceinline__ uint64_t policy_evict_first() { uint64_t p; asm volatile("createpolicy.fractional.L2::evict_first.b64 %0, 1.0;" : "=l"(p)); return p; }
__device__ __forceinline__ uint4 lds128(uint32_t a) { uint4 v; asm volatile("ld.volatile.shared.v4.u32 {%0,%1,%2,%3}, [%4];" : "=r"(v.x), "=r"(v.y), "=r"(v.z), "=r"(v.w) : "r"(a) : "memory"); return v; }
__device__ __forceinline__ void sts128(uint32_t a, uint4 v) { asm volatile("st.volatile.shared.v4.u32 [%0], {%1,%2,%3,%4};" :: "r"(a), "r"(v.x), "r"(v.y), "r"(v.z), "r"(v.w) : "memory"); }
__device__ __forceinline__ uint32_t lds32(uint32_t a) { uint32_t v; asm volatile("ld.volatile.shared.u32 %0, [%1];" : "=r"(v) : "r"(a) : "memory"); return v; }
__device__ __forceinline__ void sts32(uint32_t a, uint32_t v) { asm volatile("st.volatile.shared.u32 [%0], %1;" :: "r"(a), "r"(v) : "memory"); }
__device__ __forceinline__ uint32_t ld_relaxed(const void* p) { uint32_t v; asm volatile("ld.relaxed.gpu.global.u32 %0, [%1];" : "=r"(v) : "l"(p) : "memory"); return v; }
__device__ __forceinline__ void st_relaxed(void* p, uint32_t v) { asm volatile("st.relaxed.gpu.global.u32 [%0], %1;" :: "l"(p), "r"(v) : "memory"); }
__device__ __forceinline__ void accum(float* a, uint4 v) {
    a[0] += __uint_as_float(v.x << 16); a[1] += __uint_as_float(v.x & 0xffff0000u);
    a[2] += __uint_as_float(v.y << 16); a[3] += __uint_as_float(v.y & 0xffff0000u);
    a[4] += __uint_as_float(v.z << 16); a[5] += __uint_as_float(v.z & 0xffff0000u);
    a[6] += __uint_as_float(v.w << 16); a[7] += __uint_as_float(v.w & 0xffff0000u);
}
__device__ __forceinline__ uint32_t bmul2(uint32_t a, uint32_t b) { uint32_t d; asm("mul.rn.bf16x2 %0, %1, %2;" : "=r"(d) : "r"(a), "r"(b)); return d; }
__device__ __forceinline__ uint4 scale(uint4 v, uint4 s) { return make_uint4(bmul2(v.x, s.x), bmul2(v.y, s.y), bmul2(v.z, s.z), bmul2(v.w, s.w)); }
__device__ __forceinline__ float bf16r(float x) { return __bfloat162float(__float2bfloat16_rn(x)); }
__device__ __forceinline__ __nv_bfloat16 gate(float sum, float n, float w) {
    const float g = bf16r(__fdiv_rn(bf16r(sum), n));
    const float z = bf16r(g * w);
    return __float2bfloat16_rn(__fdiv_rn(1.f, 1.f + expf(-z)));
}
__device__ __forceinline__ uint32_t enc(float v) { return ~min(__float_as_uint(v), 0xFFFFFFFEu); }

__device__ __forceinline__ float dec(uint32_t u) { return __uint_as_float(~u); }

template <int LO, int HI> __device__ __forceinline__ void swap_block(uint4* r, int sel, uint32_t a) {
    if constexpr (HI - LO == 1) {
        uint4* v = r + (LO >> 1) * Q;
        const uint4 t = lds128(a);
        if constexpr ((LO & 1) == 0) {
#pragma unroll
            for (int k = 0; k < Q - 1; k++) { sts128(a + k * U, v[k]); v[k] = lds128(a + (k + 1) * U); }
            sts128(a + (Q - 1) * U, v[Q - 1]); v[Q - 1] = t;
        } else {
#pragma unroll
            for (int k = Q - 1; k > 0; k--) { sts128(a + ((k + 1) % Q) * U, v[k]); v[k] = lds128(a + k * U); }
            sts128(a + U, v[0]); v[0] = t;
        }
    } else {
        if (sel < (LO + HI) / 2) swap_block<LO, (LO + HI) / 2>(r, sel, a); else swap_block<(LO + HI) / 2, HI>(r, sel, a);
    }
}
template <int K> __device__ __forceinline__ void load_block(uint32_t sa, const char* src, uint32_t ga, uint64_t pol) {
    if constexpr (K < Q) {
        asm volatile("{\n.reg .pred p;\nsetp.ge.u32 p, %3, %6;\ncp.async.cg.shared.global.L2::cache_hint [%0+%4], [%1+%5], 16, p, %2;\n}"
                     :: "r"(sa), "l"(src), "l"(pol), "r"(ga), "n"(K * U), "n"(K * KSTEP), "n"(NBYTES - K * KSTEP) : "memory");
        load_block<K + 1>(sa, src, ga, pol);
    }
}
template <int K> __device__ __forceinline__ void store_block(uint32_t sa, char* dst, uint32_t ga, uint4 s4, uint64_t pol) {
    if constexpr (K < Q) {
        const uint4 v = scale(lds128(sa + K * U), s4);
        asm volatile("{\n.reg .pred p;\nsetp.lt.u32 p, %6, %8;\n@p st.global.L1::no_allocate.L2::cache_hint.v4.u32 [%0+%7], {%1,%2,%3,%4}, %5;\n}"
                     :: "l"(dst), "r"(v.x), "r"(v.y), "r"(v.z), "r"(v.w), "l"(pol), "r"(ga), "n"(K * KSTEP), "n"(NBYTES - K * KSTEP) : "memory");
        store_block<K + 1>(sa, dst, ga, s4, pol);
    }
}

__global__ void __launch_bounds__(384, 1)
eca_kernel(const char* __restrict__ x, const __nv_bfloat16* __restrict__ w1d, char* __restrict__ out, const __grid_constant__ Prog S) {
    extern __shared__ __align__(1024) char smem[];
    const uint32_t tid = threadIdx.x, lane = tid & 31, warp = tid >> 5;
    const uint32_t b = blockIdx.x;
    const uint32_t s0 = (uint32_t)__cvta_generic_to_shared(smem);
    const uint32_t tstart = now_ns();
    const uint64_t pol = policy_evict_first();
    if (warp < 8) {
        load_block<0>(opaque(s0 + tid * 16), x + (b * CSTEP + warp * WSTEP + (lane >> 4) * 768 + (lane & 15) * 16), 0, pol);
        asm volatile("cp.async.commit_group;" ::: "memory");
    } else if (tid == 256) {
        for (int g = 0; g < 3; g++) { mbar_init(s0 + BAR_PUB + g * 8, 8); mbar_init(s0 + BAR_S + g * 8, 1); }
        mbar_init(s0 + BAR_STEP, 8); mbar_init(s0 + BAR_STEP + 8, 8); mbar_init(s0 + BAR_DONE, 8);
        sts32(s0 + SHIFT_OFF, 0); sts32(s0 + LATE_OFF, 0);
    }
    __syncthreads();

    if (warp >= 8) {
        asm volatile("setmaxnreg.dec.sync.aligned.u32 %0;" :: "n"(ECA_RDEC));
        if (warp > 8 && ((const uint32_t*)S.e)[min(((lane & 7) * 3 + warp - 8) * 16, MAXSTEP * 4 + 47u)] == 0xffffffffu) sts32(s0 + LATE_OFF, 0);
        const uint32_t t = tid & 127;
        if (warp == 8) {
#pragma unroll
            for (int i = 0; i < 3; i++) *(uint4*)&g_part[(i * 16 + (lane & 15)) * PROW + b * 8 + (lane >> 4) * 4] = make_uint4(0, 0, 0, 0);
            if (b == 0 && lane == 0) g_shift[0] = 0;
            if (b < REP) { *(uint4*)&g_s[b * 256 + lane * 4] = make_uint4(0, 0, 0, 0); *(uint4*)&g_s[b * 256 + 128 + lane * 4] = make_uint4(0, 0, 0, 0); }
            __threadfence();
            __syncwarp();
            if (lane == 0) {
                const bool gen = atomicInc(&g_arrive, 2 * G - 1) >= G;
#pragma unroll 1
                for (int it = 0; it < (1 << 21); it++) {
                    if ((ld_relaxed(&g_arrive) >= G) != gen) break;
                    __nanosleep(200);
                }
                sts32(s0 + W_OFF, __float_as_uint(__bfloat162float(w1d[0])));
            }
            __syncwarp();
            __threadfence();
        }
        asm volatile("bar.sync 1, 128;" ::: "memory");
#pragma unroll 1
        for (uint32_t g = 0; g < 4; g++) {
            if (t == 32) {
#pragma unroll 1
                for (int it = 0; it < (1 << 20); it++) {
                    uint32_t late; asm volatile("atom.shared.exch.b32 %0, [%1], 0;" : "=r"(late) : "r"(s0 + LATE_OFF) : "memory");
                    const uint32_t sh = lds32(s0 + SHIFT_OFF);
                    const int ex = (int)(late - sh) - S.theta;
                    if (ex > 0) asm volatile("red.relaxed.gpu.global.max.u32 [%0], %1;" :: "l"(g_shift), "r"(sh + ((ex * S.gain) >> 6)) : "memory");
                    asm volatile("cp.async.cg.shared.global [%0], [%1], 16;" :: "r"(s0 + SHIFT_OFF), "l"(g_shift) : "memory");
                    uint32_t ok;
                    asm volatile("{\n.reg .pred p;\nmbarrier.try_wait.parity.shared::cta.b64 p, [%1], 0, %2;\nselp.u32 %0, 1, 0, p;\n}"
                                 : "=r"(ok) : "r"(s0 + BAR_PUB + g * 8), "r"(S.tau) : "memory");
                    if (ok) break;
                }
                if (g == 3) asm volatile("cp.async.wait_all;" ::: "memory");
            }
            __syncwarp();
            if (g == 3) break;
            mbar_wait(s0 + BAR_PUB + g * 8, 0);
            {
                const uint32_t a = s0 + SCR_OFF + (t >> 3) * 16 + (t & 4) * 64 + (t & 3) * 4;
                float p[8];
#pragma unroll
                for (int i = 0; i < 8; i++) p[i] = __uint_as_float(lds32(a + i * 512));
                st_relaxed(&g_part[(g * 16 + (t >> 3)) * PROW + b * 8 + (t & 7)], enc(((p[0] + p[1]) + (p[2] + p[3])) + ((p[4] + p[5]) + (p[6] + p[7]))));
            }
            ECA_STAMP(t == 0, 1 + 2 * g);
            const bool reducer = (b & 7) == 0 && b < 128;
            if (reducer) {
                const uint32_t* src = &g_part[(g * 16 + (b >> 3)) * PROW + t];
                uint32_t p[9];
#pragma unroll 1
                for (int it = 0; it < (1 << 20); it++) {
                    spin_ns(it ? S.xd2 : S.xd0);
                    ECA_STAMP(t == 0, 100 + g * 8);
#pragma unroll
                    for (int i = 0; i < 8; i++) p[i] = ld_relaxed(src + i * 128);
                    p[8] = t < G * 8 - 1024 ? ld_relaxed(src + 1024) : ~0u;
                    const uint32_t mn = min(min(min(p[0], p[1]), min(p[2], p[3])), min(min(min(p[4], p[5]), min(p[6], p[7])), p[8]));
                    ECA_PUT(t == 0, 102 + g * 8, it);
                    if (__all_sync(0xffffffffu, mn != 0)) break;
                }
                ECA_STAMP(t == 0, 101 + g * 8);
                float v = (((dec(p[0]) + dec(p[1])) + (dec(p[2]) + dec(p[3]))) + ((dec(p[4]) + dec(p[5])) + (dec(p[6]) + dec(p[7])))) + dec(p[8]);
                v += __shfl_xor_sync(0xffffffffu, v, 8); v += __shfl_xor_sync(0xffffffffu, v, 16);
                if (lane < 8) sts32(s0 + RED_OFF + (t >> 5) * 32 + lane * 4, __float_as_uint(v));
            }
            asm volatile("bar.sync 1, 128;" ::: "memory");
            if (warp == 8) {
                if (reducer) {
                    const uint32_t a = s0 + RED_OFF + (lane & 7) * 4;
                    const float v = (__uint_as_float(lds32(a)) + __uint_as_float(lds32(a + 32))) + (__uint_as_float(lds32(a + 64)) + __uint_as_float(lds32(a + 96)));
                    const uint32_t hb = __bfloat16_as_ushort(gate(v, (float)HW, __uint_as_float(lds32(s0 + W_OFF)))) & 0x7fffu;
                    const uint32_t w2 = ~(hb | (__shfl_xor_sync(0xffffffffu, hb, 1) << 16));
                    if (!(lane & 1)) st_relaxed(&g_s[(t >> 3) * 256 + g * 64 + (b >> 3) * 4 + ((t & 7) >> 1)], w2);
                    ECA_STAMP(lane == 0, 103 + g * 8);
                }
                spin_ns(reducer ? S.xd3 : S.xd1);
                uint32_t a0, a1;
#pragma unroll 1
                for (int it = 0; it < (1 << 21); it++) {
                    asm volatile("ld.relaxed.gpu.global.v2.u32 {%0,%1}, [%2];" : "=r"(a0), "=r"(a1) : "l"(&g_s[(b % REP) * 256 + g * 64 + t * 2]) : "memory");
                    ECA_PUT(lane == 0, 104 + g * 8, it);
                    if (__all_sync(0xffffffffu, a0 && a1)) break;
                    spin_ns(S.xd2);
                }
                asm volatile("st.shared.v2.u32 [%0], {%1,%2};" :: "r"(s0 + SV_OFF + g * 256 + lane * 8), "r"(~a0), "r"(~a1) : "memory");
                ECA_STAMP(lane == 0, 2 + 2 * g);
                __syncwarp();
                if (lane == 0) mbar_arrive(s0 + BAR_S + g * 8);
            }
        }
    } else {
        asm volatile("setmaxnreg.inc.sync.aligned.u32 %0;" :: "n"(ECA_RINC));
        ECA_PUT(tid == 0, 0, tstart);
        const uint32_t sbase = __shfl_sync(0xffffffffu, s0 + tid * 16, lane);
        auto fresh = [&]() { uint32_t o; asm volatile("mov.u32 %0, %1;" : "=r"(o) : "r"(sbase)); return o; };
        const uint32_t gcta = b * CSTEP - (s0 >> 9) * WSTEP;
        auto gaddr = [&](uint32_t off) { const uint32_t o = fresh(); return (o & 255) + (o & 256) * 3 + (o >> 9) * WSTEP + gcta + (off & ~127u); };
        float acc[8];
#pragma unroll
        for (int i = 0; i < 8; i++) acc[i] = 0.f;
        uint4 r[NRB * Q];
#pragma unroll
        for (int i = 0; i < NRB * Q; i++) asm volatile("" : "=r"(r[i].x), "=r"(r[i].y), "=r"(r[i].z), "=r"(r[i].w));
        uint4 s4 = make_uint4(0, 0, 0, 0);
        uint32_t js = 0;
#pragma unroll 1
        for (int j = 1; j < S.n; j++) {
            Step e;
            e.t = S.e[j].t; e.y = S.e[j].y;
            {
                const uint32_t tt = tstart + ((ECA_MAP >= 2 ? (fresh() >> 9) - (s0 >> 9) : (fresh() >> 9) * 5 + b) & 7) * S.stagger + e.t;
                const int late = (int)(now_ns() - tt);
                if (late > 0 && (sbase & 511) == 0) asm volatile("red.shared.max.u32 [%0], %1;" :: "r"(s0 + LATE_OFF), "r"(late) : "memory");
#pragma unroll 1
                for (int it = 0; it < 4096; it++) { const int d = (int)(tt + lds32(s0 + SHIFT_OFF) - now_ns()); if (d <= 0) break; if (d > 100) __nanosleep(32); }
            }
            ECA_STAMP((sbase & 4095) == 1024, 16 + j);
            if (j >= 3) mbar_wait(s0 + BAR_STEP + (j & 1) * 8, ((j - 3) >> 1) & 1);
#pragma unroll 1
            for (bool opt = true; js < (opt ? (e.y & 255) : (e.y >> 8)); opt = false) {
                const uint32_t y = S.st[js];
                if (y & 8) {
                    const int g = (y >> 4) & 3;
                    if (js < (e.y >> 8)) {
                        ECA_STAMP((sbase & 4095) == 1024, 8 + 2 * g);
                        mbar_wait(s0 + BAR_S + g * 8, 0);
                        ECA_STAMP((sbase & 4095) == 1024, 9 + 2 * g);
                    } else if (!mbar_test(s0 + BAR_S + g * 8)) break;
                    s4 = lds128(s0 + SV_OFF + g * 256 + (sbase & 255));
                }
                const uint32_t ga = gaddr(y & 0x0fffffffu);
                store_block<0>(sbase + (y >> 28) * BLK, out + ga, ga, s4, pol);
                js++;
            }
            { int jj; asm volatile("mov.u32 %0, %1;" : "=r"(jj) : "r"(j)); e.x = S.e[jj].x; e.z = S.e[jj].z; }
            if (e.x & 1) {
                const uint32_t ga = gaddr(e.x);
                const char* src = x + ga;
                load_block<0>(opaque(sbase + (e.z & 15) * BLK), src, ga, pol);
                if ((e.x & 2) && (sbase & 127) == 0) {
#pragma unroll
                    for (int k = 0; k < Q; k++)
                        asm volatile("prefetch.global.L2 [%0];" :: "l"(src + k * KSTEP) : "memory");
                }
            }
            asm volatile("cp.async.commit_group;" ::: "memory");
            asm volatile("cp.async.wait_group %0;" :: "n"(LAG) : "memory");
            if (e.z & (1u << 12)) {
                const uint32_t sa = sbase + ((e.z >> 4) & 15) * BLK;
#pragma unroll
                for (int k = 0; k < Q; k++) accum(acc, lds128(sa + k * U));
            }
            if (e.z & (1u << 14)) {
                const int g = (e.z >> 8) & 3;
                const bool h = sbase & 256;
                float k0 = h ? acc[4] : acc[0], k1 = h ? acc[5] : acc[1], k2 = h ? acc[6] : acc[2], k3 = h ? acc[7] : acc[3];
                k0 += __shfl_xor_sync(0xffffffffu, h ? acc[0] : acc[4], 16); k1 += __shfl_xor_sync(0xffffffffu, h ? acc[1] : acc[5], 16);
                k2 += __shfl_xor_sync(0xffffffffu, h ? acc[2] : acc[6], 16); k3 += __shfl_xor_sync(0xffffffffu, h ? acc[3] : acc[7], 16);
                if (g) mbar_wait(s0 + BAR_S - 8 + g * 8, 0);
                sts128(sbase + SCR_OFF, make_uint4(__float_as_uint(k0), __float_as_uint(k1), __float_as_uint(k2), __float_as_uint(k3)));
                __syncwarp();
                if ((sbase & 511) == 0) mbar_arrive(s0 + BAR_PUB + g * 8);
#pragma unroll
                for (int i = 0; i < 8; i++) acc[i] = 0.f;
            }
            if (e.z & (1u << 13)) swap_block<0, 2 * NRB>(r, e.z >> 20, sbase + ((e.z >> 16) & 15) * BLK);
            __syncwarp();
            if ((sbase & 511) == 0) {
                mbar_arrive(s0 + BAR_STEP + (j & 1) * 8);
                if (e.z & (1u << 15)) mbar_arrive(s0 + BAR_DONE);
            }
        }
    }
}

struct Plan {
    int nL2;
    int dPoll;
    int nAbs;
    int absSteps;
    int tFirst, tL;
    int tS1, tS2, n1, n2;
    int tF1, tF2, nF;
    int tE, nE;
    int stagger;
    int xd0, xd1, xd2, xd3;
    int theta, gain, tau;
    int l2pos;
    int wAt, tW, tWR, tL2;
    int early;
    int tL0;
};
static inline uint32_t enc_block(int t) { return (uint32_t)(t % BPG) * BSTEP + (t / BPG) * 256 + 1; }

static bool build_program(const Plan& P, Prog& prog) {
    memset(&prog, 0, sizeof(prog));
    prog.stagger = P.stagger; prog.xd0 = P.xd0; prog.xd1 = P.xd1; prog.xd2 = P.xd2; prog.xd3 = P.xd3; prog.theta = P.theta; prog.gain = P.gain; prog.tau = P.tau;
    int blk[NB], ready[NB], kind[NB], reg[NRB], par[NRB], accAt[MAXSTEP + LAG + 1];
    for (int k = 0; k < NB; k++) { blk[k] = -1; ready[k] = 0; kind[k] = 0; }
    for (int k = 0; k < NRB; k++) { reg[k] = -1; par[k] = 0; }
    for (int k = 0; k < MAXSTEP + LAG + 1; k++) accAt[k] = -1;
    int pubAt[4] = {1 << 20, 1 << 20, 1 << 20, 1 << 20}, remain[3] = {BPG, BPG, BPG};
    if (P.l2pos + P.nL2 >= BPG) return false;
    const int E = NBLK - NB - NRB - P.nL2;
    int li = 0, l2next = 0, stored = 0, sg = -1;
    int avail[NBLK], mode[MAXSTEP];
    int j = 0;
    for (;; j++) {
        if (j >= MAXSTEP) return false;
        Step e = {0, 0, 0, 0};
        const bool readsDone = li >= NBLK;
        int nfree = 0, fb = -1;
        if (stored == NBLK) break;
        if ((sg < 0 || remain[sg] == 0) && j > pubAt[sg + 1]) sg++;
        for (int k = 0; k < NB; k++) nfree += blk[k] < 0;
        const bool wmode = !readsDone && stored >= P.wAt && stored < E && (nfree == 0 || stored > P.wAt);
        mode[j] = readsDone ? 3 : wmode ? 1 : (stored == E && E > P.wAt) ? 2 : 0;
        bool extra = false;
        for (int g = 0; g < 3; g++) extra |= j == pubAt[g] && (P.early >> g & 1);
        if (extra) mode[j] = 4;
        bool did = false;
        if ((readsDone || wmode || nfree == 0) && sg >= 0 && !extra) {
            int best = -1;
            for (int k = 0; k < NB; k++)
                if (blk[k] >= 0 && blk[k] / BPG == sg && ready[k] < j && kind[k] != 1) {
                    if (best < 0 || (kind[k] == 2) > (kind[best] == 2) || ((kind[k] == 2) == (kind[best] == 2) && blk[k] < blk[best])) best = k;
                }
            if (best >= 0) {
                prog.st[stored] = (enc_block(blk[best]) & ~1u) | (remain[sg] == BPG ? 8 : 0) | sg << 4 | (uint32_t)best << 28;
                avail[stored] = ready[best] + 1 > pubAt[sg] + 1 ? ready[best] + 1 : pubAt[sg] + 1;
                blk[best] = -1; remain[sg]--; stored++; did = true;
            }
        }
        e.y = stored << 8;
        for (int k = NB - 1; k >= 0; k--) if (blk[k] < 0) fb = k;
        if (extra) {
        } else if (wmode) {
            if (!did) return false;
        } else if (!readsDone) {
            if (fb < 0) return false;
            const bool l2 = li >= BPG + P.l2pos && li < BPG + P.l2pos + P.nL2;
            e.x = enc_block(li) | (l2 ? 2 : 0); e.z |= fb;
            blk[fb] = li; ready[fb] = j + LAG; kind[fb] = l2; accAt[j + LAG] = fb;
            if (li % BPG == BPG - 1) pubAt[li / BPG] = j + LAG;
            li++;
        } else if (l2next < P.nL2 && fb >= 0) {
            e.x = enc_block(BPG + P.l2pos + l2next); e.z |= fb;
            blk[fb] = BPG + P.l2pos + l2next; ready[fb] = j + LAG; kind[fb] = 2;
            l2next++;
        }
        if (accAt[j] >= 0) { e.z |= accAt[j] << 4 | 1u << 12; if (kind[accAt[j]] == 1) blk[accAt[j]] = -1; }
        {
            int eb = -1, mb = -1, best = -1;
            nfree = 0; fb = -1;
            for (int i = NRB - 1; i >= 0; i--) { if (reg[i] < 0) eb = i; else if (mb < 0 || reg[i] < reg[mb]) mb = i; }
            for (int k = NB - 1; k >= 0; k--) {
                if (blk[k] < 0) { nfree++; fb = k; }
                else if (ready[k] <= j && kind[k] == 0 && (best < 0 || blk[k] > blk[best])) best = k;
            }
            int sb = -1, sk = -1;
            if (li < NBLK && nfree == 0 && eb >= 0 && best >= 0) { sb = eb; sk = best; }
            else if (mb >= 0 && best >= 0 && reg[mb] / BPG < blk[best] / BPG) { sb = mb; sk = best; }
            else if (((li >= NBLK && l2next >= P.nL2) || (wmode && mb >= 0 && reg[mb] / BPG < 2)) && mb >= 0 && fb >= 0) { sb = mb; sk = fb; }
            if (sb >= 0) { e.z |= 1u << 13 | sk << 16 | (sb * 2 + par[sb]) << 20; par[sb] ^= 1; const int tmp = reg[sb]; reg[sb] = blk[sk]; blk[sk] = tmp; ready[sk] = j; kind[sk] = 0; }
        }
        for (int g = 0; g < 3; g++) if (j == pubAt[g]) e.z |= 1u << 14 | g << 8;
        prog.e[j] = e;
    }
    prog.n = j;
    prog.e[j - 3].z |= 1u << 15;
    double credit = 0.999, t = 0;
    int want = 0;
    for (j = 0; j < prog.n; j++) {
        const int need = prog.e[j].y >> 8, before = want, start = pubAt[0] + P.dPoll;
        if (j >= start && mode[j] == 0 && want < E && want < P.wAt) {
            credit += j < start + P.absSteps ? (double)P.nAbs / P.absSteps : 1.0;
            if (credit > 1.999) credit = 1.999;
            if (credit >= 1.0 && avail[want] <= j) want++;
        }
        if (want < need) want = need;
        if (want > before) credit -= 1.0;
        prog.e[j].y |= want;
        if (mode[j] == 4) { prog.e[j].t = prog.e[j - 1].t; prog.e[j].y = prog.e[j - 1].y >> 8 | (prog.e[j - 1].y & ~255u); continue; }
        prog.e[j].t = (uint32_t)t;
        if (mode[j] == 1) t += P.tW + (want == E ? P.tWR : 0);
        else if (mode[j] != 3) t += j == 0 ? P.tFirst : mode[j] == 2 ? P.tL2 : want == 0 ? P.tL0 : P.tL;
        if (want > before && mode[j] != 1) {
            const double f = mode[j] == 3 ? (want - E - 1) / (double)P.nF : (want - P.n1) / (double)(P.n2 - P.n1);
            const double c = f < 0 ? 0 : f > 1 ? 1 : f;
            t += want >= NBLK - P.nE ? P.tE : mode[j] == 3 ? P.tF1 + c * (P.tF2 - P.tF1) : P.tS1 + c * (P.tS2 - P.tS1);
        }
    }
    return prog.e[0].x == enc_block(0) && prog.e[0].z == 0;
}

static const Plan kPlan = {4,5,5,11,46,869,70,1441,4,17,954,664,1,783,15,112,781,2209,0,1532,848,10,1368,5,9,743,262,908,0,862};

constexpr int FB_BLOCKS = 256, FB_MAXC = 4096;
__device__ float g_fb_part[FB_BLOCKS * FB_MAXC / 8];
__device__ __nv_bfloat16 g_fb_s[FB_MAXC];
__global__ void fb_sum(const __nv_bfloat16* __restrict__ x, int rows) {
    for (int c = threadIdx.x; c < C; c += blockDim.x) {
        float a = 0.f;
        for (int r = blockIdx.x; r < rows; r += gridDim.x) a += __bfloat162float(x[(size_t)r * C + c]);
        g_fb_part[blockIdx.x * C + c] = a;
    }
}
__global__ void fb_gate(const __nv_bfloat16* __restrict__ w1d, int rows) {
    for (int c = threadIdx.x; c < C; c += blockDim.x) {
        float a = 0.f;
        for (int i = 0; i < FB_BLOCKS; i++) a += g_fb_part[i * C + c];
        g_fb_s[c] = gate(a, (float)rows, __bfloat162float(w1d[0]));
    }
}
__global__ void fb_scale(const __nv_bfloat16* __restrict__ x, __nv_bfloat16* __restrict__ out, size_t n) {
    for (size_t i = blockIdx.x * (size_t)blockDim.x + threadIdx.x; i < n; i += (size_t)gridDim.x * blockDim.x) out[i] = __hmul(x[i], g_fb_s[i % C]);
}

}

extern "C" void kernel_launch(void* const* d_in, const int* in_sizes, int n_in, void* d_out, int out_size) {
    using namespace eca;
    (void)n_in; (void)out_size;
    static int mode = -1;
    static Prog prog;
    if (mode < 0) {
        int dev = 0, sms = 0, occ = 0;
        cudaGetDevice(&dev);
        cudaDeviceGetAttribute(&sms, cudaDevAttrMultiProcessorCount, dev);
        bool ok = cudaFuncSetAttribute(eca_kernel, cudaFuncAttributeMaxDynamicSharedMemorySize, SMEM_BYTES) == cudaSuccess;
        ok = ok && cudaOccupancyMaxActiveBlocksPerMultiprocessor(&occ, eca_kernel, 384, SMEM_BYTES) == cudaSuccess;
        ok = ok && occ >= 1 && sms >= G && build_program(kPlan, prog);
        (void)cudaGetLastError();
        mode = ok ? 1 : 0;
    }
    const __nv_bfloat16* x = (const __nv_bfloat16*)d_in[0];
    const __nv_bfloat16* w = (const __nv_bfloat16*)d_in[1];
    const bool aligned = (((uintptr_t)x | (uintptr_t)d_out) & 15) == 0;
    if (mode == 1 && in_sizes[0] == HW * C && aligned) {
        eca_kernel<<<G, 384, SMEM_BYTES, cudaStreamPerThread>>>((const char*)x, w, (char*)d_out, prog);
    } else {
        const int rows = in_sizes[0] / C;
        fb_sum<<<FB_BLOCKS, 384, 0, cudaStreamPerThread>>>(x, rows);
        fb_gate<<<1, 384, 0, cudaStreamPerThread>>>(w, rows);
        fb_scale<<<1024, 256, 0, cudaStreamPerThread>>>(x, (__nv_bfloat16*)d_out, (size_t)in_sizes[0]);
    }
}
```

```cpp
#include <cuda_runtime.h>
#include <cuda_bf16.h>
#include <stdint.h>
#include <string.h>

namespace eca {

constexpr int C = 384, HW = 384 * 384;
constexpr int G = 132;
constexpr int REP = 4;
constexpr int U = 4096;
constexpr int Q = 5;
constexpr int BLK = Q * U;
constexpr int NB = 11;
constexpr int NRB = 10;
constexpr int BPG = 14;
constexpr int NBLK = 3 * BPG;
constexpr int LAG = 2;
constexpr int MAXSTEP = 84;
constexpr int SHIFT_FRAC = 13;
constexpr uint32_t CSTEP = 2 * 768, KSTEP = G * CSTEP, WSTEP = Q * KSTEP, BSTEP = 8 * WSTEP;
constexpr uint32_t NBYTES = (uint32_t)HW * C * 2;
constexpr uint32_t SCR_OFF = NB * BLK, RED_OFF = SCR_OFF + 4096, SV_OFF = RED_OFF + 128, BAR_OFF = SV_OFF + 768, SMEM_BYTES = BAR_OFF + 128;
constexpr uint32_t BAR_PUB = BAR_OFF, BAR_DONE = BAR_PUB + 24, BAR_S = BAR_OFF + 32, BAR_STEP = BAR_OFF + 64, W_OFF = BAR_OFF + 96, LATE_OFF = BAR_OFF + 100, SHIFT_OFF = BAR_OFF + 112;

struct __align__(16) Step { uint32_t t, y, x, z; };
struct Prog { int n, stagger, xd0, xd1, xd2, xd3, theta, gain, tau, cap, pad1, pad2; Step e[MAXSTEP]; uint32_t st[48]; };

constexpr uint32_t PROW = (G + 4) * 8;
__device__ __align__(256) uint32_t g_part[48 * PROW];
__device__ __align__(256) uint32_t g_s[REP * 256];
__device__ __align__(256) unsigned g_shift[4];
__device__ __align__(256) unsigned g_arrive;

__device__ __forceinline__ uint32_t now_ns() { uint32_t t; asm volatile("mov.u32 %0, %globaltimer_lo;" : "=r"(t)); return t; }
__device__ __forceinline__ void mbar_init(uint32_t bar, uint32_t cnt) { asm volatile("mbarrier.init.shared::cta.b64 [%0], %1;" :: "r"(bar), "r"(cnt) : "memory"); }
__device__ __forceinline__ void mbar_arrive(uint32_t bar) { asm volatile("mbarrier.arrive.shared::cta.b64 _, [%0];" :: "r"(bar) : "memory"); }
__device__ __forceinline__ void mbar_wait(uint32_t bar, uint32_t parity) {
#pragma unroll 1
    for (int i = 0; i < (1 << 21); i++) {
        uint32_t ok;
        asm volatile("{\n.reg .pred p;\nmbarrier.try_wait.parity.shared::cta.b64 p, [%1], %2, 1000;\nselp.u32 %0, 1, 0, p;\n}"
                     : "=r"(ok) : "r"(bar), "r"(parity) : "memory");
        if (ok) return;
    }
}
__device__ __forceinline__ bool mbar_test(uint32_t bar) {
    uint32_t ok;
    asm volatile("{\n.reg .pred p;\nmbarrier.test_wait.parity.shared::cta.b64 p, [%1], 0;\nselp.u32 %0, 1, 0, p;\n}" : "=r"(ok) : "r"(bar) : "memory");
    return ok;
}
__device__ __forceinline__ void spin_ns(uint32_t ns) {
    const uint32_t a = now_ns();
#pragma unroll 1
    for (int it = 0; it < 256; it++) { if (now_ns() - a >= ns) break; __nanosleep(32); }
}
__device__ __forceinline__ uint32_t opaque(uint32_t a) { uint32_t t; asm volatile("max.u32 %0, %1, 16;" : "=r"(t) : "r"(a)); return t; }
__device__ __forceinline__ uint64_t policy_evict_first() { uint64_t p; asm volatile("createpolicy.fractional.L2::evict_first.b64 %0, 1.0;" : "=l"(p)); return p; }
__device__ __forceinline__ uint4 lds128(uint32_t a) { uint4 v; asm volatile("ld.volatile.shared.v4.u32 {%0,%1,%2,%3}, [%4];" : "=r"(v.x), "=r"(v.y), "=r"(v.z), "=r"(v.w) : "r"(a) : "memory"); return v; }
__device__ __forceinline__ void sts128(uint32_t a, uint4 v) { asm volatile("st.volatile.shared.v4.u32 [%0], {%1,%2,%3,%4};" :: "r"(a), "r"(v.x), "r"(v.y), "r"(v.z), "r"(v.w) : "memory"); }
__device__ __forceinline__ uint32_t lds32(uint32_t a) { uint32_t v; asm volatile("ld.volatile.shared.u32 %0, [%1];" : "=r"(v) : "r"(a) : "memory"); return v; }
__device__ __forceinline__ void sts32(uint32_t a, uint32_t v) { asm volatile("st.volatile.shared.u32 [%0], %1;" :: "r"(a), "r"(v) : "memory"); }
__device__ __forceinline__ uint32_t ld_relaxed(const void* p) { uint32_t v; asm volatile("ld.relaxed.gpu.global.u32 %0, [%1];" : "=r"(v) : "l"(p) : "memory"); return v; }
__device__ __forceinline__ void st_relaxed(void* p, uint32_t v) { asm volatile("st.relaxed.gpu.global.u32 [%0], %1;" :: "l"(p), "r"(v) : "memory"); }
__device__ __forceinline__ void accum(float* a, uint4 v) {
    a[0] += __uint_as_float(v.x << 16); a[1] += __uint_as_float(v.x & 0xffff0000u);
    a[2] += __uint_as_float(v.y << 16); a[3] += __uint_as_float(v.y & 0xffff0000u);
    a[4] += __uint_as_float(v.z << 16); a[5] += __uint_as_float(v.z & 0xffff0000u);
    a[6] += __uint_as_float(v.w << 16); a[7] += __uint_as_float(v.w & 0xffff0000u);
}
__device__ __forceinline__ uint32_t bmul2(uint32_t a, uint32_t b) { uint32_t d; asm("mul.rn.bf16x2 %0, %1, %2;" : "=r"(d) : "r"(a), "r"(b)); return d; }
__device__ __forceinline__ uint4 scale(uint4 v, uint4 s) { return make_uint4(bmul2(v.x, s.x), bmul2(v.y, s.y), bmul2(v.z, s.z), bmul2(v.w, s.w)); }
__device__ __forceinline__ float bf16r(float x) { return __bfloat162float(__float2bfloat16_rn(x)); }
__device__ __forceinline__ __nv_bfloat16 gate(float sum, float n, float w) {
    const float g = bf16r(__fdiv_rn(bf16r(sum), n));
    const float z = bf16r(g * w);
    return __float2bfloat16_rn(__fdiv_rn(1.f, 1.f + expf(-z)));
}
__device__ __forceinline__ uint32_t enc(float v) { return ~min(__float_as_uint(v), 0xFFFFFFFEu); }

__device__ __forceinline__ float dec(uint32_t u) { return __uint_as_float(~u); }

template <int LO, int HI> __device__ __forceinline__ void swap_block(uint4* r, int sel, uint32_t a) {
    if constexpr (HI - LO == 1) {
        uint4* v = r + (LO >> 1) * Q;
        const uint4 t = lds128(a);
        if constexpr ((LO & 1) == 0) {
#pragma unroll
            for (int k = 0; k < Q - 1; k++) { sts128(a + k * U, v[k]); v[k] = lds128(a + (k + 1) * U); }
            sts128(a + (Q - 1) * U, v[Q - 1]); v[Q - 1] = t;
        } else {
#pragma unroll
            for (int k = Q - 1; k > 0; k--) { sts128(a + ((k + 1) % Q) * U, v[k]); v[k] = lds128(a + k * U); }
            sts128(a + U, v[0]); v[0] = t;
        }
    } else {
        if (sel < (LO + HI) / 2) swap_block<LO, (LO + HI) / 2>(r, sel, a); else swap_block<(LO + HI) / 2, HI>(r, sel, a);
    }
}
template <int K> __device__ __forceinline__ void load_block(uint32_t sa, const char* src, uint32_t ga, uint64_t pol) {
    if constexpr (K < Q) {
        asm volatile("{\n.reg .pred p;\nsetp.ge.u32 p, %3, %6;\ncp.async.cg.shared.global.L2::cache_hint [%0+%4], [%1+%5], 16, p, %2;\n}"
                     :: "r"(sa), "l"(src), "l"(pol), "r"(ga), "n"(K * U), "n"(K * KSTEP), "n"(NBYTES - K * KSTEP) : "memory");
        load_block<K + 1>(sa, src, ga, pol);
    }
}
template <int K> __device__ __forceinline__ void store_block(uint32_t sa, char* dst, uint32_t ga, uint4 s4, uint64_t pol) {
    if constexpr (K < Q) {
        const uint4 v = scale(lds128(sa + K * U), s4);
        asm volatile("{\n.reg .pred p;\nsetp.lt.u32 p, %6, %8;\n@p st.global.L1::no_allocate.L2::cache_hint.v4.u32 [%0+%7], {%1,%2,%3,%4}, %5;\n}"
                     :: "l"(dst), "r"(v.x), "r"(v.y), "r"(v.z), "r"(v.w), "l"(pol), "r"(ga), "n"(K * KSTEP), "n"(NBYTES - K * KSTEP) : "memory");
        store_block<K + 1>(sa, dst, ga, s4, pol);
    }
}

__global__ void __launch_bounds__(384, 1)
eca_kernel(const char* __restrict__ x, const __nv_bfloat16* __restrict__ w1d, char* __restrict__ out, const __grid_constant__ Prog S) {
    extern __shared__ __align__(1024) char smem[];
    const uint32_t tid = threadIdx.x, lane = tid & 31, warp = tid >> 5;
    const uint32_t b = blockIdx.x;
    const uint32_t s0 = (uint32_t)__cvta_generic_to_shared(smem);
    const uint32_t tstart = now_ns();
    const uint64_t pol = policy_evict_first();
    if (warp < 8) {
        load_block<0>(opaque(s0 + tid * 16), x + (b * CSTEP + warp * WSTEP + (lane >> 4) * 768 + (lane & 15) * 16), 0, pol);
        asm volatile("cp.async.commit_group;" ::: "memory");
    } else if (tid == 256) {
        for (int g = 0; g < 3; g++) { mbar_init(s0 + BAR_PUB + g * 8, 8); mbar_init(s0 + BAR_S + g * 8, 1); }
        mbar_init(s0 + BAR_STEP, 8); mbar_init(s0 + BAR_STEP + 8, 8); mbar_init(s0 + BAR_DONE, 8);
        sts32(s0 + SHIFT_OFF, 0); sts32(s0 + LATE_OFF, 0);
    }
    __syncthreads();

    if (warp >= 8) {
        asm volatile("setmaxnreg.dec.sync.aligned.u32 %0;" :: "n"(24));
        if (warp > 8 && ((const uint32_t*)S.e)[min(((lane & 7) * 3 + warp - 8) * 16, MAXSTEP * 4 + 47u)] == 0xffffffffu) sts32(s0 + LATE_OFF, 0);
        const uint32_t t = tid & 127;
        if (warp == 8) {
#pragma unroll
            for (int i = 0; i < 3; i++) *(uint4*)&g_part[(i * 16 + (lane & 15)) * PROW + b * 8 + (lane >> 4) * 4] = make_uint4(0, 0, 0, 0);
            if (b == 0 && lane == 0) g_shift[0] = 0;
            if (b < REP) { *(uint4*)&g_s[b * 256 + lane * 4] = make_uint4(0, 0, 0, 0); *(uint4*)&g_s[b * 256 + 128 + lane * 4] = make_uint4(0, 0, 0, 0); }
            __threadfence();
            __syncwarp();
            if (lane == 0) {
                const bool gen = atomicInc(&g_arrive, 2 * G - 1) >= G;
#pragma unroll 1
                for (int it = 0; it < (1 << 21); it++) {
                    spin_ns(it ? 500 : 2500);
                    if ((ld_relaxed(&g_arrive) >= G) != gen) break;
                }
                sts32(s0 + W_OFF, __float_as_uint(__bfloat162float(w1d[0])));
            }
            __syncwarp();
            __threadfence();
        }
        asm volatile("bar.sync 1, 128;" ::: "memory");
#pragma unroll 1
        for (uint32_t g = 0; g < 4; g++) {
            if (t == 32) {
#pragma unroll 1
                for (int it = 0; it < (1 << 20); it++) {
                    uint32_t late; asm volatile("atom.shared.exch.b32 %0, [%1], 0;" : "=r"(late) : "r"(s0 + LATE_OFF) : "memory");
                    const int ex = (int)(late - (lds32(s0 + SHIFT_OFF) >> SHIFT_FRAC)) - S.theta;
                    if (ex > 0) asm volatile("red.relaxed.gpu.global.add.u32 [%0], %1;" :: "l"(g_shift), "r"(min(ex, S.cap) * S.gain) : "memory");
                    asm volatile("cp.async.cg.shared.global [%0], [%1], 16;" :: "r"(s0 + SHIFT_OFF), "l"(g_shift) : "memory");
                    uint32_t ok;
                    asm volatile("{\n.reg .pred p;\nmbarrier.try_wait.parity.shared::cta.b64 p, [%1], 0, %2;\nselp.u32 %0, 1, 0, p;\n}"
                                 : "=r"(ok) : "r"(s0 + BAR_PUB + g * 8), "r"(S.tau) : "memory");
                    if (ok) break;
                }
                if (g == 3) asm volatile("cp.async.wait_all;" ::: "memory");
            }
            __syncwarp();
            if (g == 3) break;
            mbar_wait(s0 + BAR_PUB + g * 8, 0);
            {
                const uint32_t a = s0 + SCR_OFF + (t >> 3) * 16 + (t & 4) * 64 + (t & 3) * 4;
                float p[8];
#pragma unroll
                for (int i = 0; i < 8; i++) p[i] = __uint_as_float(lds32(a + i * 512));
                st_relaxed(&g_part[(g * 16 + (t >> 3)) * PROW + b * 8 + (t & 7)], enc(((p[0] + p[1]) + (p[2] + p[3])) + ((p[4] + p[5]) + (p[6] + p[7]))));
            }
            const bool reducer = (b & 7) == 0 && b < 128;
            if (reducer) {
                const uint32_t* src = &g_part[(g * 16 + (b >> 3)) * PROW + t];
                uint32_t p[9];
#pragma unroll 1
                for (int it = 0; it < (1 << 20); it++) {
                    spin_ns(it ? S.xd2 : S.xd0);
#pragma unroll
                    for (int i = 0; i < 8; i++) p[i] = ld_relaxed(src + i * 128);
                    p[8] = t < G * 8 - 1024 ? ld_relaxed(src + 1024) : ~0u;
                    const uint32_t mn = min(min(min(p[0], p[1]), min(p[2], p[3])), min(min(min(p[4], p[5]), min(p[6], p[7])), p[8]));
                    if (__all_sync(0xffffffffu, mn != 0)) break;
                }
                float v = (((dec(p[0]) + dec(p[1])) + (dec(p[2]) + dec(p[3]))) + ((dec(p[4]) + dec(p[5])) + (dec(p[6]) + dec(p[7])))) + dec(p[8]);
                v += __shfl_xor_sync(0xffffffffu, v, 8); v += __shfl_xor_sync(0xffffffffu, v, 16);
                if (lane < 8) sts32(s0 + RED_OFF + (t >> 5) * 32 + lane * 4, __float_as_uint(v));
            }
            asm volatile("bar.sync 1, 128;" ::: "memory");
            if (warp == 8) {
                if (reducer) {
                    const uint32_t a = s0 + RED_OFF + (lane & 7) * 4;
                    const float v = (__uint_as_float(lds32(a)) + __uint_as_float(lds32(a + 32))) + (__uint_as_float(lds32(a + 64)) + __uint_as_float(lds32(a + 96)));
                    const uint32_t hb = __bfloat16_as_ushort(gate(v, (float)HW, __uint_as_float(lds32(s0 + W_OFF)))) & 0x7fffu;
                    const uint32_t w2 = ~(hb | (__shfl_xor_sync(0xffffffffu, hb, 1) << 16));
                    if (!(lane & 1)) st_relaxed(&g_s[(t >> 3) * 256 + g * 64 + (b >> 3) * 4 + ((t & 7) >> 1)], w2);
                }
                spin_ns(reducer ? S.xd3 : S.xd1);
                uint32_t a0, a1;
#pragma unroll 1
                for (int it = 0; it < (1 << 21); it++) {
                    asm volatile("ld.relaxed.gpu.global.v2.u32 {%0,%1}, [%2];" : "=r"(a0), "=r"(a1) : "l"(&g_s[(b % REP) * 256 + g * 64 + t * 2]) : "memory");
                    if (__all_sync(0xffffffffu, a0 && a1)) break;
                    spin_ns(S.xd2);
                }
                asm volatile("st.shared.v2.u32 [%0], {%1,%2};" :: "r"(s0 + SV_OFF + g * 256 + lane * 8), "r"(~a0), "r"(~a1) : "memory");
                __syncwarp();
                if (lane == 0) mbar_arrive(s0 + BAR_S + g * 8);
            }
        }
    } else {
        asm volatile("setmaxnreg.inc.sync.aligned.u32 %0;" :: "n"(240));
        const uint32_t sbase = __shfl_sync(0xffffffffu, s0 + tid * 16, lane);
        auto fresh = [&]() { uint32_t o; asm volatile("mov.u32 %0, %1;" : "=r"(o) : "r"(sbase)); return o; };
        const uint32_t gcta = b * CSTEP - (s0 >> 9) * WSTEP;
        auto gaddr = [&](uint32_t off) { const uint32_t o = fresh(); return (o & 255) + (o & 256) * 3 + (o >> 9) * WSTEP + gcta + (off & ~127u); };
        float acc[8];
#pragma unroll
        for (int i = 0; i < 8; i++) acc[i] = 0.f;
        uint4 r[NRB * Q];
#pragma unroll
        for (int i = 0; i < NRB * Q; i++) asm volatile("" : "=r"(r[i].x), "=r"(r[i].y), "=r"(r[i].z), "=r"(r[i].w));
        uint4 s4 = make_uint4(0, 0, 0, 0);
        uint32_t js = 0;
#pragma unroll 1
        for (int j = 1; j < S.n; j++) {
            Step e;
            e.t = S.e[j].t; e.y = S.e[j].y;
            {
                const uint32_t tt = tstart + ((fresh() >> 9) - (s0 >> 9)) * S.stagger + e.t;
                const uint32_t now = now_ns();
                int d = (int)(tt + (lds32(s0 + SHIFT_OFF) >> SHIFT_FRAC) - now);
                asm volatile("{\n.reg .pred p;\nsetp.lt.s32 p, %2, 0;\n@p red.shared.max.u32 [%0], %1;\n}"
                             :: "r"(s0 + LATE_OFF), "r"(now - tt), "r"((sbase & 511) == 0 ? d : 0) : "memory");
#pragma unroll 1
                for (int it = 0; d > 0 && it < 4096; it++) { if (d > 100) __nanosleep(32); d = (int)(tt + (lds32(s0 + SHIFT_OFF) >> SHIFT_FRAC) - now_ns()); }
            }
            if (j >= 3) mbar_wait(s0 + BAR_STEP + (j & 1) * 8, ((j - 3) >> 1) & 1);
#pragma unroll 1
            for (bool opt = true; js < (opt ? (e.y & 255) : (e.y >> 8)); opt = false) {
                const uint32_t y = S.st[js];
                if (y & 8) {
                    const int g = (y >> 4) & 3;
                    if (js < (e.y >> 8)) mbar_wait(s0 + BAR_S + g * 8, 0);
                    else if (!mbar_test(s0 + BAR_S + g * 8)) break;
                    s4 = lds128(s0 + SV_OFF + g * 256 + (sbase & 255));
                }
                const uint32_t ga = gaddr(y & 0x0fffffffu);
                store_block<0>(sbase + (y >> 28) * BLK, out + ga, ga, s4, pol);
                js++;
            }
            { int jj; asm volatile("mov.u32 %0, %1;" : "=r"(jj) : "r"(j)); e.x = S.e[jj].x; e.z = S.e[jj].z; }
            if (e.x & 1) {
                const uint32_t ga = gaddr(e.x);
                const char* src = x + ga;
                load_block<0>(opaque(sbase + (e.z & 15) * BLK), src, ga, pol);
                if ((e.x & 2) && (sbase & 127) == 0) {
#pragma unroll
                    for (int k = 0; k < Q; k++)
                        asm volatile("prefetch.global.L2 [%0];" :: "l"(src + k * KSTEP) : "memory");
                }
            }
            asm volatile("cp.async.commit_group;" ::: "memory");
            if (e.z & (1u << 11)) asm volatile("cp.async.wait_group %0;" :: "n"(LAG) : "memory");
            if (e.z & (1u << 12)) {
                const uint32_t sa = sbase + ((e.z >> 4) & 15) * BLK;
#pragma unroll
                for (int k = 0; k < Q; k++) accum(acc, lds128(sa + k * U));
            }
            if (e.z & (1u << 14)) {
                const int g = (e.z >> 8) & 3;
                const bool h = sbase & 256;
                float k0 = h ? acc[4] : acc[0], k1 = h ? acc[5] : acc[1], k2 = h ? acc[6] : acc[2], k3 = h ? acc[7] : acc[3];
                k0 += __shfl_xor_sync(0xffffffffu, h ? acc[0] : acc[4], 16); k1 += __shfl_xor_sync(0xffffffffu, h ? acc[1] : acc[5], 16);
                k2 += __shfl_xor_sync(0xffffffffu, h ? acc[2] : acc[6], 16); k3 += __shfl_xor_sync(0xffffffffu, h ? acc[3] : acc[7], 16);
                if (g) mbar_wait(s0 + BAR_S - 8 + g * 8, 0);
                sts128(sbase + SCR_OFF, make_uint4(__float_as_uint(k0), __float_as_uint(k1), __float_as_uint(k2), __float_as_uint(k3)));
                __syncwarp();
                if ((sbase & 511) == 0) mbar_arrive(s0 + BAR_PUB + g * 8);
#pragma unroll
                for (int i = 0; i < 8; i++) acc[i] = 0.f;
            }
            if (e.z & (1u << 13)) swap_block<0, 2 * NRB>(r, e.z >> 20, sbase + ((e.z >> 16) & 15) * BLK);
            __syncwarp();
            if ((sbase & 511) == 0) {
                mbar_arrive(s0 + BAR_STEP + (j & 1) * 8);
                if (e.z & (1u << 15)) mbar_arrive(s0 + BAR_DONE);
            }
        }
    }
}

struct Plan {
    int nL2;
    int dPoll;
    int nAbs;
    int absSteps;
    int tFirst, tL;
    int tS1, tS2, n1, n2;
    int tF1, tF2, nF;
    int tE, nE;
    int stagger;
    int xd0, xd1, xd2, xd3;
    int theta, gain, tau;
    int l2pos;
    int wAt, tW, tWR, tL2;
    int tL0;
    int nZ, tZ;
    int cap;
    int nEarly;
};
static inline uint32_t enc_block(int t) { return (uint32_t)(t % BPG) * BSTEP + (t / BPG) * 256 + 1; }

static bool build_program(const Plan& P, Prog& prog, double tscale = 1.0) {
    memset(&prog, 0, sizeof(prog));
    prog.stagger = (int)(P.stagger * tscale); prog.xd0 = P.xd0; prog.xd1 = P.xd1; prog.xd2 = P.xd2; prog.xd3 = P.xd3; prog.theta = P.theta; prog.gain = P.gain; prog.tau = P.tau; prog.cap = P.cap;
    int blk[NB], ready[NB], kind[NB], reg[NRB], par[NRB], accAt[MAXSTEP + LAG];
    for (int k = 0; k < NB; k++) { blk[k] = -1; ready[k] = 0; kind[k] = 0; }
    for (int k = 0; k < NRB; k++) { reg[k] = -1; par[k] = 0; }
    for (int k = 0; k < MAXSTEP + LAG; k++) accAt[k] = -1;
    int pubAt[4] = {1 << 20, 1 << 20, 1 << 20, 1 << 20}, remain[3] = {BPG, BPG, BPG};
    if (P.l2pos + P.nL2 >= BPG) return false;
    if (P.nEarly > P.nL2) return false;
    const int E = NBLK - NB - NRB - (P.nL2 - P.nEarly);
    int li = 0, l2next = 0, stored = 0, sg = -1;
    int avail[NBLK], mode[MAXSTEP];
    int j = 0;
    for (;; j++) {
        if (j >= MAXSTEP) return false;
        Step e = {0, 0, 0, 0};
        const bool readsDone = li >= NBLK;
        int nfree = 0, fb = -1;
        if (stored == NBLK) break;
        if ((sg < 0 || remain[sg] == 0) && j > pubAt[sg + 1]) sg++;
        for (int k = 0; k < NB; k++) nfree += blk[k] < 0;
        const bool wmode = !readsDone && stored >= P.wAt && stored < E && (nfree == 0 || stored > P.wAt);
        mode[j] = readsDone ? 3 : wmode ? 1 : (stored == E && E > P.wAt) ? 2 : 0;
        bool did = false;
        if ((readsDone || wmode || nfree == 0) && sg >= 0) {
            int best = -1;
            for (int k = 0; k < NB; k++)
                if (blk[k] >= 0 && blk[k] / BPG == sg && ready[k] < j && kind[k] != 1) {
                    if (best < 0 || (kind[k] == 2) < (kind[best] == 2) || ((kind[k] == 2) == (kind[best] == 2) && blk[k] < blk[best])) best = k;
                }
            if (best >= 0) {
                prog.st[stored] = (enc_block(blk[best]) & ~1u) | (remain[sg] == BPG ? 8 : 0) | sg << 4 | (uint32_t)best << 28;
                avail[stored] = ready[best] + 1 > pubAt[sg] + 1 ? ready[best] + 1 : pubAt[sg] + 1;
                bool waited = kind[best] != 2;
                for (int q = ready[best]; q < j; q++) waited |= prog.e[q].z >> 11 & 1;
                if (!waited) prog.e[j - 1].z |= 1u << 11;
                if (kind[best] == 2) avail[stored] = j;
                blk[best] = -1; remain[sg]--; stored++; did = true;
            }
        }
        e.y = stored << 8;
        for (int k = NB - 1; k >= 0; k--) if (blk[k] < 0) fb = k;
        if (wmode && (!did || l2next >= P.nEarly)) {
            if (!did) return false;
        } else if (!readsDone && !wmode) {
            if (fb < 0) return false;
            const bool l2 = (li >= BPG + P.l2pos && li < BPG + P.l2pos + P.nL2);
            e.x = enc_block(li) | (l2 ? 2 : 0); e.z |= fb;
            blk[fb] = li; ready[fb] = j + LAG; kind[fb] = l2; accAt[j + LAG] = fb;
            if (li % BPG == BPG - 1) pubAt[li / BPG] = j + LAG;
            li++;
        } else if (l2next < P.nL2 && fb >= 0) {
            const int t = BPG + P.l2pos + l2next;
            e.x = enc_block(t); e.z |= fb;
            blk[fb] = t; ready[fb] = j + LAG; kind[fb] = 2;
            l2next++;
        }
        if (accAt[j] >= 0) { e.z |= accAt[j] << 4 | 3u << 11; if (kind[accAt[j]] == 1) blk[accAt[j]] = -1; }
        {
            int eb = -1, mb = -1, best = -1;
            nfree = 0; fb = -1;
            for (int i = NRB - 1; i >= 0; i--) { if (reg[i] < 0) eb = i; else if (mb < 0 || reg[i] < reg[mb]) mb = i; }
            for (int k = NB - 1; k >= 0; k--) {
                if (blk[k] < 0) { nfree++; fb = k; }
                else if (ready[k] <= j && kind[k] == 0 && (best < 0 || blk[k] > blk[best])) best = k;
            }
            int sb = -1, sk = -1;
            if (li < NBLK && nfree == 0 && eb >= 0 && best >= 0) { sb = eb; sk = best; }
            else if (mb >= 0 && best >= 0 && reg[mb] / BPG < blk[best] / BPG) { sb = mb; sk = best; }
            else if (((li >= NBLK && l2next >= P.nL2) || (wmode && l2next >= P.nEarly && nfree + E - stored > LAG + 1 && mb >= 0 && reg[mb] / BPG < 2)) && mb >= 0 && fb >= 0) { sb = mb; sk = fb; }
            if (sb >= 0) { e.z |= 1u << 13 | sk << 16 | (sb * 2 + par[sb]) << 20; par[sb] ^= 1; const int tmp = reg[sb]; reg[sb] = blk[sk]; blk[sk] = tmp; ready[sk] = j; kind[sk] = 0; }
        }
        for (int g = 0; g < 3; g++) if (j == pubAt[g]) e.z |= 1u << 14 | g << 8;
        prog.e[j] = e;
    }
    prog.n = j;
    prog.e[j - 3].z |= 1u << 15;
    double credit = 0.999, t = 0;
    int want = 0;
    for (j = 0; j < prog.n; j++) {
        const int need = prog.e[j].y >> 8, before = want, start = pubAt[0] + P.dPoll;
        if (j >= start && mode[j] == 0 && want < E && want < P.wAt) {
            credit += j < start + P.absSteps ? (double)P.nAbs / P.absSteps : 1.0;
            if (credit > 1.999) credit = 1.999;
            if (credit >= 1.0 && avail[want] <= j) want++;
        }
        if (want < need) want = need;
        if (want > before) credit -= 1.0;
        prog.e[j].y |= want;
        prog.e[j].t = (uint32_t)(t * tscale);
        if (mode[j] == 1) t += P.tW + (want == E ? P.tWR : 0);
        else if (mode[j] != 3) t += j == 0 ? P.tFirst : mode[j] == 2 ? P.tL2 : want == 0 ? P.tL0 : P.tL;
        if (want > before && mode[j] != 1) {
            const double f = mode[j] == 3 ? (want - E - 1) / (double)P.nF : (want - P.n1) / (double)(P.n2 - P.n1);
            const double c = f < 0 ? 0 : f > 1 ? 1 : f;
            t += want >= NBLK - P.nZ ? P.tZ : want >= NBLK - P.nE ? P.tE : mode[j] == 3 ? P.tF1 + c * (P.tF2 - P.tF1) : P.tS1 + c * (P.tS2 - P.tS1);
        }
    }
    return prog.e[0].x == enc_block(0) && prog.e[0].z == 0;
}

static const Plan kPlan = {5,5,6,14,68,855,0,1671,4,19,704,665,3,817,14,102,869,2290,0,437,119,20,696,4,8,683,487,920,843,2,570,3454,2};

constexpr int FB_BLOCKS = 1024;
__device__ float g_fb_part[FB_BLOCKS * C];
__device__ __nv_bfloat16 g_fb_s[C];
__global__ void fb_sum(const __nv_bfloat16* __restrict__ x, int rows) {
    for (int c = threadIdx.x; c < C; c += blockDim.x) {
        float a = 0.f;
        for (int r = blockIdx.x; r < rows; r += gridDim.x) a += __bfloat162float(x[(size_t)r * C + c]);
        g_fb_part[blockIdx.x * C + c] = a;
    }
}
__global__ void fb_gate(const __nv_bfloat16* __restrict__ w1d, int rows) {
    for (int c = threadIdx.x; c < C; c += blockDim.x) {
        float a = 0.f;
        for (int i = 0; i < FB_BLOCKS; i++) a += g_fb_part[i * C + c];
        g_fb_s[c] = gate(a, (float)rows, __bfloat162float(w1d[0]));
    }
}
__global__ void fb_scale(const __nv_bfloat16* __restrict__ x, __nv_bfloat16* __restrict__ out, size_t n) {
    for (size_t i = blockIdx.x * (size_t)blockDim.x + threadIdx.x; i < n; i += (size_t)gridDim.x * blockDim.x) out[i] = __hmul(x[i], g_fb_s[i % C]);
}

}

extern "C" void kernel_launch(void* const* d_in, const int* in_sizes, int n_in, void* d_out, int out_size) {
    using namespace eca;
    (void)n_in; (void)out_size;
    static int mode = -1;
    static Prog prog;
    if (mode < 0) {
        int dev = 0, sms = 0, occ = 0, coop = 0, khz = 0, bits = 0;
        cudaGetDevice(&dev);
        cudaDeviceGetAttribute(&sms, cudaDevAttrMultiProcessorCount, dev);
        cudaDeviceGetAttribute(&coop, cudaDevAttrCooperativeLaunch, dev);
        cudaDeviceGetAttribute(&khz, cudaDevAttrMemoryClockRate, dev);
        cudaDeviceGetAttribute(&bits, cudaDevAttrGlobalMemoryBusWidth, dev);
        double tscale = khz > 0 && bits > 0 ? 2619000.0 * 5120.0 / ((double)khz * bits) : 1.0;
        if (tscale < 0.5 || tscale > 2.0) tscale = 1.0;
        bool ok = cudaFuncSetAttribute(eca_kernel, cudaFuncAttributeMaxDynamicSharedMemorySize, SMEM_BYTES) == cudaSuccess;
        ok = ok && cudaOccupancyMaxActiveBlocksPerMultiprocessor(&occ, eca_kernel, 384, SMEM_BYTES) == cudaSuccess;
        ok = ok && coop && occ >= 1 && sms >= G && build_program(kPlan, prog, tscale);
        (void)cudaGetLastError();
        mode = ok ? 1 : 0;
    }
    const char* x = (const char*)d_in[0];
    const __nv_bfloat16* w = (const __nv_bfloat16*)d_in[1];
    char* out = (char*)d_out;
    if (mode == 1 && in_sizes[0] == HW * C && (((uintptr_t)x | (uintptr_t)out) & 15) == 0) {
        void* args[4] = {&x, &w, &out, &prog};
        cudaLaunchCooperativeKernel((const void*)eca_kernel, dim3(G), dim3(384), args, SMEM_BYTES, cudaStreamPerThread);
    } else {
        const int rows = in_sizes[0] / C;
        fb_sum<<<FB_BLOCKS, 384, 0, cudaStreamPerThread>>>((const __nv_bfloat16*)x, rows);
        fb_gate<<<1, 384, 0, cudaStreamPerThread>>>(w, rows);
        fb_scale<<<1024, 256, 0, cudaStreamPerThread>>>((const __nv_bfloat16*)x, (__nv_bfloat16*)out, (size_t)in_sizes[0]);
    }
}
```

```cpp
#include <cuda_runtime.h>
#include <cuda_bf16.h>
#include <stdint.h>
#include <string.h>

namespace eca {

constexpr int C = 384, HW = 384 * 384;
constexpr int G = 132;
constexpr int REP = 4;
constexpr int U = 4096;
constexpr int Q = 5;
constexpr int BLK = Q * U;
constexpr int NB = 11;
constexpr int NRB = 10;
constexpr int BPG = 14;
constexpr int NBLK = 3 * BPG;
constexpr int LAG = 2;
constexpr int NL1 = 2;
constexpr int MAXSTEP = 84;
constexpr int SHIFT_FRAC = 13;
constexpr uint32_t CSTEP = 2 * 768, KSTEP = G * CSTEP, WSTEP = Q * KSTEP, BSTEP = 8 * WSTEP;
constexpr uint32_t NBYTES = (uint32_t)HW * C * 2;
constexpr uint32_t SCR_OFF = NB * BLK, RED_OFF = SCR_OFF + 4096, SV_OFF = RED_OFF + 128, BAR_OFF = SV_OFF + 768, SMEM_BYTES = BAR_OFF + 128;
constexpr uint32_t BAR_PUB = BAR_OFF, BAR_DONE = BAR_PUB + 24, BAR_S = BAR_OFF + 32, BAR_STEP = BAR_OFF + 64, W_OFF = BAR_OFF + 96, LATE_OFF = BAR_OFF + 100, SHIFT_OFF = BAR_OFF + 112;

struct __align__(16) Step { uint32_t t, y, x, z; };
struct Prog { int n, stagger, xd0, xd1, xd2, xd3, theta, gain, tau, cap, pad1, pad2; Step e[MAXSTEP]; uint32_t st[48]; };

constexpr uint32_t PROW = (G + 4) * 8;
__device__ __align__(256) uint32_t g_part[48 * PROW];
__device__ __align__(256) uint32_t g_s[REP * 256];
__device__ __align__(256) unsigned g_shift[4];
__device__ __align__(256) unsigned g_arrive;

__device__ __forceinline__ uint32_t now_ns() { uint32_t t; asm volatile("mov.u32 %0, %globaltimer_lo;" : "=r"(t)); return t; }
__device__ __forceinline__ void mbar_init(uint32_t bar, uint32_t cnt) { asm volatile("mbarrier.init.shared::cta.b64 [%0], %1;" :: "r"(bar), "r"(cnt) : "memory"); }
__device__ __forceinline__ void mbar_arrive(uint32_t bar) { asm volatile("mbarrier.arrive.shared::cta.b64 _, [%0];" :: "r"(bar) : "memory"); }
__device__ __forceinline__ void mbar_wait(uint32_t bar, uint32_t parity) {
#pragma unroll 1
    for (int i = 0; i < (1 << 21); i++) {
        uint32_t ok;
        asm volatile("{\n.reg .pred p;\nmbarrier.try_wait.parity.shared::cta.b64 p, [%1], %2, 1000;\nselp.u32 %0, 1, 0, p;\n}"
                     : "=r"(ok) : "r"(bar), "r"(parity) : "memory");
        if (ok) return;
    }
}
__device__ __forceinline__ bool mbar_test(uint32_t bar) {
    uint32_t ok;
    asm volatile("{\n.reg .pred p;\nmbarrier.test_wait.parity.shared::cta.b64 p, [%1], 0;\nselp.u32 %0, 1, 0, p;\n}" : "=r"(ok) : "r"(bar) : "memory");
    return ok;
}
__device__ __forceinline__ void spin_ns(uint32_t ns) {
    const uint32_t a = now_ns();
#pragma unroll 1
    for (int it = 0; it < 256; it++) { if (now_ns() - a >= ns) break; __nanosleep(32); }
}
__device__ __forceinline__ uint32_t opaque(uint32_t a) { uint32_t t; asm volatile("max.u32 %0, %1, 16;" : "=r"(t) : "r"(a)); return t; }
__device__ __forceinline__ uint64_t policy_evict_first() { uint64_t p; asm volatile("createpolicy.fractional.L2::evict_first.b64 %0, 1.0;" : "=l"(p)); return p; }
__device__ __forceinline__ uint4 lds128(uint32_t a) { uint4 v; asm volatile("ld.volatile.shared.v4.u32 {%0,%1,%2,%3}, [%4];" : "=r"(v.x), "=r"(v.y), "=r"(v.z), "=r"(v.w) : "r"(a) : "memory"); return v; }
__device__ __forceinline__ void sts128(uint32_t a, uint4 v) { asm volatile("st.volatile.shared.v4.u32 [%0], {%1,%2,%3,%4};" :: "r"(a), "r"(v.x), "r"(v.y), "r"(v.z), "r"(v.w) : "memory"); }
__device__ __forceinline__ uint32_t lds32(uint32_t a) { uint32_t v; asm volatile("ld.volatile.shared.u32 %0, [%1];" : "=r"(v) : "r"(a) : "memory"); return v; }
__device__ __forceinline__ void sts32(uint32_t a, uint32_t v) { asm volatile("st.volatile.shared.u32 [%0], %1;" :: "r"(a), "r"(v) : "memory"); }
__device__ __forceinline__ uint32_t ld_relaxed(const void* p) { uint32_t v; asm volatile("ld.relaxed.gpu.global.u32 %0, [%1];" : "=r"(v) : "l"(p) : "memory"); return v; }
__device__ __forceinline__ void st_relaxed(void* p, uint32_t v) { asm volatile("st.relaxed.gpu.global.u32 [%0], %1;" :: "l"(p), "r"(v) : "memory"); }
__device__ __forceinline__ void accum(float* a, uint32_t addr) {
    uint32_t x, y; asm volatile("ld.volatile.shared.v2.u32 {%0,%1}, [%2];" : "=r"(x), "=r"(y) : "r"(addr) : "memory");
    a[0] += __uint_as_float(x << 16); a[1] += __uint_as_float(x & 0xffff0000u);
    a[2] += __uint_as_float(y << 16); a[3] += __uint_as_float(y & 0xffff0000u);
}
__device__ __forceinline__ uint32_t bmul2(uint32_t a, uint32_t b) { uint32_t d; asm("mul.rn.bf16x2 %0, %1, %2;" : "=r"(d) : "r"(a), "r"(b)); return d; }
__device__ __forceinline__ uint4 scale(uint4 v, uint4 s) { return make_uint4(bmul2(v.x, s.x), bmul2(v.y, s.y), bmul2(v.z, s.z), bmul2(v.w, s.w)); }
__device__ __forceinline__ float bf16r(float x) { return __bfloat162float(__float2bfloat16_rn(x)); }
__device__ __forceinline__ __nv_bfloat16 gate(float sum, float n, float w) {
    const float g = bf16r(__fdiv_rn(bf16r(sum), n));
    const float z = bf16r(g * w);
    return __float2bfloat16_rn(__frcp_rn(1.f + expf(-z)));
}
__device__ __forceinline__ uint32_t enc(float v) { return ~min(__float_as_uint(v), 0xFFFFFFFEu); }

__device__ __forceinline__ float dec(uint32_t u) { return __uint_as_float(~u); }

template <int LO, int HI> __device__ __forceinline__ void swap_block(uint4* r, int sel, uint32_t a) {
    if constexpr (HI - LO == 1) {
        uint4* v = r + (LO >> 1) * Q;
        const uint4 t = lds128(a);
        if constexpr ((LO & 1) == 0) {
#pragma unroll
            for (int k = 0; k < Q - 1; k++) { sts128(a + k * U, v[k]); v[k] = lds128(a + (k + 1) * U); }
            sts128(a + (Q - 1) * U, v[Q - 1]); v[Q - 1] = t;
        } else {
#pragma unroll
            for (int k = Q - 1; k > 0; k--) { sts128(a + ((k + 1) % Q) * U, v[k]); v[k] = lds128(a + k * U); }
            sts128(a + U, v[0]); v[0] = t;
        }
    } else {
        if (sel < (LO + HI) / 2) swap_block<LO, (LO + HI) / 2>(r, sel, a); else swap_block<(LO + HI) / 2, HI>(r, sel, a);
    }
}
template <int K> __device__ __forceinline__ void load_block(uint32_t sa, const char* src, uint32_t ga, uint64_t pol) {
    if constexpr (K < Q) {
        asm volatile("{\n.reg .pred p;\nsetp.ge.u32 p, %3, %6;\ncp.async.cg.shared.global.L2::cache_hint [%0+%4], [%1+%5], 16, p, %2;\n}"
                     :: "r"(sa), "l"(src), "l"(pol), "r"(ga), "n"(K * U), "n"(K * KSTEP), "n"(NBYTES - K * KSTEP) : "memory");
        load_block<K + 1>(sa, src, ga, pol);
    }
}
template <int K> __device__ __forceinline__ void load_block_l1(uint32_t sa, const char* src, uint32_t ga, uint64_t pol) {
    if constexpr (K < NL1) {
        asm volatile("cp.async.ca.shared.global.L2::cache_hint [%0+%3], [%1+%4], 16, %2;" :: "r"(sa), "l"(src), "l"(pol), "n"(K * U), "n"(K * KSTEP) : "memory");
        load_block_l1<K + 1>(sa, src, ga, pol);
    } else load_block<K>(sa, src, ga, pol);
}
template <int K> __device__ __forceinline__ void store_block(uint32_t sa, char* dst, uint32_t ga, uint4 s4, uint64_t pol) {
    if constexpr (K < Q) {
        const uint4 v = scale(lds128(sa + K * U), s4);
        asm volatile("{\n.reg .pred p;\nsetp.lt.u32 p, %6, %8;\n@p st.global.L1::no_allocate.L2::cache_hint.v4.u32 [%0+%7], {%1,%2,%3,%4}, %5;\n}"
                     :: "l"(dst), "r"(v.x), "r"(v.y), "r"(v.z), "r"(v.w), "l"(pol), "r"(ga), "n"(K * KSTEP), "n"(NBYTES - K * KSTEP) : "memory");
        store_block<K + 1>(sa, dst, ga, s4, pol);
    }
}

__global__ void __launch_bounds__(384, 1)
eca_kernel(const char* __restrict__ x, const __nv_bfloat16* __restrict__ w1d, char* __restrict__ out, const __grid_constant__ Prog S) {
    extern __shared__ __align__(1024) char smem[];
    const uint32_t tid = threadIdx.x, lane = tid & 31, warp = tid >> 5;
    const uint32_t b = blockIdx.x;
    const uint32_t s0 = (uint32_t)__cvta_generic_to_shared(smem);
    const uint32_t tstart = now_ns();
    const uint64_t pol = policy_evict_first();
    if (warp < 8) {
        load_block<0>(opaque(s0 + tid * 16), x + (b * CSTEP + warp * WSTEP + (lane >> 4) * 768 + (lane & 15) * 16), 0, pol);
        asm volatile("cp.async.commit_group;" ::: "memory");
    } else if (tid == 256) {
        for (int g = 0; g < 3; g++) { mbar_init(s0 + BAR_PUB + g * 8, 8); mbar_init(s0 + BAR_S + g * 8, 1); }
        mbar_init(s0 + BAR_STEP, 8); mbar_init(s0 + BAR_STEP + 8, 8); mbar_init(s0 + BAR_DONE, 8);
        sts32(s0 + SHIFT_OFF, 0); sts32(s0 + LATE_OFF, 0);
    }
    __syncthreads();

    if (warp >= 8) {
        asm volatile("setmaxnreg.dec.sync.aligned.u32 %0;" :: "n"(24));
        if (warp > 8 && ((const uint32_t*)S.e)[min(((lane & 7) * 3 + warp - 8) * 16, MAXSTEP * 4 + 47u)] == 0xffffffffu) sts32(s0 + LATE_OFF, 0);
        const uint32_t t = tid & 127;
        if (warp == 8) {
#pragma unroll
            for (int i = 0; i < 3; i++) *(uint4*)&g_part[(i * 16 + (lane & 15)) * PROW + b * 8 + (lane >> 4) * 4] = make_uint4(0, 0, 0, 0);
            if (b == 0 && lane == 0) g_shift[0] = 0;
            if (b < REP) { *(uint4*)&g_s[b * 256 + lane * 4] = make_uint4(0, 0, 0, 0); *(uint4*)&g_s[b * 256 + 128 + lane * 4] = make_uint4(0, 0, 0, 0); }
            __threadfence();
            __syncwarp();
            if (lane == 0) {
                const bool gen = atomicInc(&g_arrive, 2 * G - 1) >= G;
#pragma unroll 1
                for (int it = 0; it < (1 << 21); it++) {
                    spin_ns(it ? 500 : 2500);
                    if ((ld_relaxed(&g_arrive) >= G) != gen) break;
                }
                sts32(s0 + W_OFF, __float_as_uint(__bfloat162float(w1d[0])));
            }
            __syncwarp();
            __threadfence();
        }
        asm volatile("bar.sync 1, 128;" ::: "memory");
#pragma unroll 1
        for (uint32_t g = 0; g < 4; g++) {
            if (t == 32) {
#pragma unroll 1
                for (int it = 0; it < (1 << 20); it++) {
                    uint32_t late; asm volatile("atom.shared.exch.b32 %0, [%1], 0;" : "=r"(late) : "r"(s0 + LATE_OFF) : "memory");
                    const int ex = (int)(late - (lds32(s0 + SHIFT_OFF) >> SHIFT_FRAC)) - S.theta;
                    if (ex > 0) asm volatile("red.relaxed.gpu.global.add.u32 [%0], %1;" :: "l"(g_shift), "r"(min(ex, S.cap) * S.gain) : "memory");
                    asm volatile("cp.async.cg.shared.global [%0], [%1], 16;" :: "r"(s0 + SHIFT_OFF), "l"(g_shift) : "memory");
                    uint32_t ok;
                    asm volatile("{\n.reg .pred p;\nmbarrier.try_wait.parity.shared::cta.b64 p, [%1], 0, %2;\nselp.u32 %0, 1, 0, p;\n}"
                                 : "=r"(ok) : "r"(s0 + BAR_PUB + g * 8), "r"(S.tau) : "memory");
                    if (ok) break;
                }
                if (g == 3) asm volatile("cp.async.wait_all;" ::: "memory");
            }
            __syncwarp();
            if (g == 3) break;
            mbar_wait(s0 + BAR_PUB + g * 8, 0);
            {
                const uint32_t a = s0 + SCR_OFF + t * 4;
                float p[8];
#pragma unroll
                for (int i = 0; i < 8; i++) p[i] = __uint_as_float(lds32(a + i * 512));
                st_relaxed(&g_part[(g * 16 + (t >> 3)) * PROW + b * 8 + (t & 7)], enc(((p[0] + p[1]) + (p[2] + p[3])) + ((p[4] + p[5]) + (p[6] + p[7]))));
            }
            const bool reducer = (b & 7) == 0 && b < 128;
            if (reducer) {
                const uint32_t* src = &g_part[(g * 16 + (b >> 3)) * PROW + t];
                uint32_t p[9];
#pragma unroll 1
                for (int it = 0; it < (1 << 20); it++) {
                    spin_ns(it ? S.xd2 : S.xd0);
#pragma unroll
                    for (int i = 0; i < 8; i++) p[i] = ld_relaxed(src + i * 128);
                    p[8] = t < G * 8 - 1024 ? ld_relaxed(src + 1024) : ~0u;
                    const uint32_t mn = min(min(min(p[0], p[1]), min(p[2], p[3])), min(min(min(p[4], p[5]), min(p[6], p[7])), p[8]));
                    if (__all_sync(0xffffffffu, mn != 0)) break;
                }
                float v = (((dec(p[0]) + dec(p[1])) + (dec(p[2]) + dec(p[3]))) + ((dec(p[4]) + dec(p[5])) + (dec(p[6]) + dec(p[7])))) + dec(p[8]);
                v += __shfl_xor_sync(0xffffffffu, v, 8); v += __shfl_xor_sync(0xffffffffu, v, 16);
                if (lane < 8) sts32(s0 + RED_OFF + (t >> 5) * 32 + lane * 4, __float_as_uint(v));
            }
            asm volatile("bar.sync 1, 128;" ::: "memory");
            if (warp == 8) {
                if (reducer) {
                    const uint32_t a = s0 + RED_OFF + (lane & 7) * 4;
                    const float v = (__uint_as_float(lds32(a)) + __uint_as_float(lds32(a + 32))) + (__uint_as_float(lds32(a + 64)) + __uint_as_float(lds32(a + 96)));
                    const uint32_t hb = __bfloat16_as_ushort(gate(v, (float)HW, __uint_as_float(lds32(s0 + W_OFF)))) & 0x7fffu;
                    const uint32_t w2 = ~(hb | (__shfl_xor_sync(0xffffffffu, hb, 1) << 16));
                    if (!(lane & 1)) st_relaxed(&g_s[(t >> 3) * 256 + g * 64 + (b >> 3) * 4 + ((t & 7) >> 1)], w2);
                }
                spin_ns(reducer ? S.xd3 : S.xd1);
                uint32_t a0, a1;
#pragma unroll 1
                for (int it = 0; it < (1 << 21); it++) {
                    asm volatile("ld.relaxed.gpu.global.v2.u32 {%0,%1}, [%2];" : "=r"(a0), "=r"(a1) : "l"(&g_s[(b % REP) * 256 + g * 64 + t * 2]) : "memory");
                    if (__all_sync(0xffffffffu, a0 && a1)) break;
                    spin_ns(S.xd2);
                }
                asm volatile("st.shared.v2.u32 [%0], {%1,%2};" :: "r"(s0 + SV_OFF + g * 256 + lane * 8), "r"(~a0), "r"(~a1) : "memory");
                __syncwarp();
                if (lane == 0) mbar_arrive(s0 + BAR_S + g * 8);
            }
        }
    } else {
        asm volatile("setmaxnreg.inc.sync.aligned.u32 %0;" :: "n"(240));
        const uint32_t sbase = __shfl_sync(0xffffffffu, s0 + tid * 16, lane);
        auto fresh = [&]() { uint32_t o; asm volatile("mov.u32 %0, %1;" : "=r"(o) : "r"(sbase)); return o; };
        const uint32_t gcta = b * CSTEP - (s0 >> 9) * WSTEP;
        auto gaddr = [&](uint32_t off) { const uint32_t o = fresh(); return (o & 255) + (o & 256) * 3 + (o >> 9) * WSTEP + gcta + (off & ~127u); };
        float acc[4] = {0.f, 0.f, 0.f, 0.f};
        uint4 r[NRB * Q];
#pragma unroll
        for (int i = 0; i < NRB * Q; i++) asm volatile("" : "=r"(r[i].x), "=r"(r[i].y), "=r"(r[i].z), "=r"(r[i].w));
        uint4 s4 = make_uint4(0, 0, 0, 0);
        uint32_t js = 0;
#pragma unroll 1
        for (int j = 1; j < S.n; j++) {
            Step e;
            e.t = S.e[j].t; e.y = S.e[j].y;
            {
                const uint32_t tt = tstart + ((fresh() >> 9) - (s0 >> 9)) * S.stagger + e.t;
                const uint32_t now = now_ns();
                int d = (int)(tt + (lds32(s0 + SHIFT_OFF) >> SHIFT_FRAC) - now);
                asm volatile("{\n.reg .pred p;\nsetp.lt.s32 p, %2, 0;\n@p red.shared.max.u32 [%0], %1;\n}"
                             :: "r"(s0 + LATE_OFF), "r"(now - tt), "r"((sbase & 511) == 0 ? d : 0) : "memory");
#pragma unroll 1
                for (int it = 0; d > 0 && it < 4096; it++) { if (d > 100) __nanosleep(32); d = (int)(tt + (lds32(s0 + SHIFT_OFF) >> SHIFT_FRAC) - now_ns()); }
            }
            if (j >= 3) mbar_wait(s0 + BAR_STEP + (j & 1) * 8, ((j - 3) >> 1) & 1);
#pragma unroll 1
            for (bool opt = true; js < (opt ? (e.y & 255) : (e.y >> 8)); opt = false) {
                const uint32_t y = S.st[js];
                if (y & 8) {
                    const int g = (y >> 4) & 3;
                    if (js < (e.y >> 8)) mbar_wait(s0 + BAR_S + g * 8, 0);
                    else if (!mbar_test(s0 + BAR_S + g * 8)) break;
                    s4 = lds128(s0 + SV_OFF + g * 256 + (sbase & 255));
                }
                const uint32_t ga = gaddr(y & 0x0fffffffu);
                store_block<0>(sbase + (y >> 28) * BLK, out + ga, ga, s4, pol);
                js++;
            }
            { int jj; asm volatile("mov.u32 %0, %1;" : "=r"(jj) : "r"(j)); e.x = S.e[jj].x; e.z = S.e[jj].z; }
            if (e.x & 1) {
                const uint32_t ga = gaddr(e.x);
                const char* src = x + ga;
                if (e.x & 4) load_block_l1<0>(opaque(sbase + (e.z & 15) * BLK), src, ga, pol);
                else load_block<0>(opaque(sbase + (e.z & 15) * BLK), src, ga, pol);
                if ((e.x & 2) && (sbase & 127) == 0) {
#pragma unroll
                    for (int k = 0; k < Q; k++)
                        if (k >= NL1 || !(e.x & 4)) asm volatile("prefetch.global.L2 [%0];" :: "l"(src + k * KSTEP) : "memory");
                }
            }
            asm volatile("cp.async.commit_group;" ::: "memory");
            if (e.z & (1u << 11)) asm volatile("cp.async.wait_group %0;" :: "n"(LAG) : "memory");
            if (e.z & (1u << 12)) {
                const uint32_t o = fresh(), sa = (o & ~511u) + ((o & 511) >> 1) + ((e.z >> 4) & 15) * BLK;
                __syncwarp();
#pragma unroll
                for (int k = 0; k < Q; k++) { accum(acc, sa + k * U); accum(acc, sa + k * U + 256); }
                __syncwarp();
            }
            if (e.z & (1u << 14)) {
                const int g = (e.z >> 8) & 3;
                if (g) mbar_wait(s0 + BAR_S - 8 + g * 8, 0);
                sts128(sbase + SCR_OFF, make_uint4(__float_as_uint(acc[0]), __float_as_uint(acc[1]), __float_as_uint(acc[2]), __float_as_uint(acc[3])));
                __syncwarp();
                if ((sbase & 511) == 0) mbar_arrive(s0 + BAR_PUB + g * 8);
#pragma unroll
                for (int i = 0; i < 4; i++) acc[i] = 0.f;
            }
            if (e.z & (1u << 13)) swap_block<0, 2 * NRB>(r, e.z >> 20, sbase + ((e.z >> 16) & 15) * BLK);
            __syncwarp();
            if ((sbase & 511) == 0) {
                mbar_arrive(s0 + BAR_STEP + (j & 1) * 8);
                if (e.z & (1u << 15)) mbar_arrive(s0 + BAR_DONE);
            }
        }
    }
}

struct Plan {
    int nL2;
    int dPoll;
    int nAbs, absSteps;
    int tFirst, tL;
    int tS1, tS2, n1, n2;
    int tF1, tF2, nF;
    int tE, nE;
    int stagger;
    int xd0, xd1, xd2, xd3;
    int theta, gain, tau;
    int l2pos;
    int wAt, tW, tWR, tL2;
    int tL0;
    int nZ, tZ;
    int cap;
    int nEarly;
};
static inline uint32_t enc_block(int t) { return (uint32_t)(t % BPG) * BSTEP + (t / BPG) * 256 + 1; }

static bool build_program(const Plan& P, Prog& prog, double tscale = 1.0) {
    memset(&prog, 0, sizeof(prog));
    prog.stagger = (int)(P.stagger * tscale); prog.xd0 = P.xd0; prog.xd1 = P.xd1; prog.xd2 = P.xd2; prog.xd3 = P.xd3;
    prog.theta = P.theta; prog.gain = P.gain; prog.tau = P.tau; prog.cap = P.cap;
    int blk[NB], ready[NB], kind[NB], reg[NRB], par[NRB], accAt[MAXSTEP + LAG];
    for (int k = 0; k < NB; k++) { blk[k] = -1; ready[k] = 0; kind[k] = 0; }
    for (int k = 0; k < NRB; k++) { reg[k] = -1; par[k] = 0; }
    for (int k = 0; k < MAXSTEP + LAG; k++) accAt[k] = -1;
    int pubAt[4] = {1 << 20, 1 << 20, 1 << 20, 1 << 20}, remain[3] = {BPG, BPG, BPG};
    if (P.l2pos + P.nL2 >= BPG) return false;
    if (P.nEarly > P.nL2) return false;
    const int E = NBLK - NB - NRB - (P.nL2 - P.nEarly);
    int li = 0, l2next = 0, stored = 0, sg = -1;
    int avail[NBLK], mode[MAXSTEP];
    int j = 0;
    for (;; j++) {
        if (j >= MAXSTEP) return false;
        Step e = {0, 0, 0, 0};
        const bool readsDone = li >= NBLK;
        int nfree = 0, fb = -1;
        if (stored == NBLK) break;
        if ((sg < 0 || remain[sg] == 0) && j > pubAt[sg + 1]) sg++;
        for (int k = 0; k < NB; k++) nfree += blk[k] < 0;
        const bool wmode = !readsDone && stored >= P.wAt && stored < E && (nfree == 0 || stored > P.wAt);
        mode[j] = readsDone ? 3 : wmode ? 1 : (stored == E && E > P.wAt) ? 2 : 0;
        bool did = false;
        if ((readsDone || wmode || nfree == 0) && sg >= 0) {
            int best = -1;
            for (int k = 0; k < NB; k++)
                if (blk[k] >= 0 && blk[k] / BPG == sg && ready[k] < j && kind[k] != 1) {
                    if (best < 0 || (kind[k] == 2) < (kind[best] == 2) || ((kind[k] == 2) == (kind[best] == 2) && blk[k] < blk[best])) best = k;
                }
            if (best >= 0) {
                prog.st[stored] = (enc_block(blk[best]) & ~1u) | (remain[sg] == BPG ? 8 : 0) | sg << 4 | (uint32_t)best << 28;
                avail[stored] = ready[best] + 1 > pubAt[sg] + 1 ? ready[best] + 1 : pubAt[sg] + 1;
                bool waited = kind[best] != 2;
                for (int q = ready[best]; q < j; q++) waited |= prog.e[q].z >> 11 & 1;
                if (!waited) prog.e[j - 1].z |= 1u << 11;
                if (kind[best] == 2) avail[stored] = j;
                blk[best] = -1; remain[sg]--; stored++; did = true;
            }
        }
        e.y = stored << 8;
        for (int k = NB - 1; k >= 0; k--) if (blk[k] < 0) fb = k;
        if (wmode && (!did || l2next >= P.nEarly)) {
            if (!did) return false;
        } else if (!readsDone && !wmode) {
            if (fb < 0) return false;
            const bool l2 = (li >= BPG + P.l2pos && li < BPG + P.l2pos + P.nL2);
            e.x = enc_block(li) | (l2 ? 2 : 0) | (li == BPG + P.l2pos + P.nL2 - 1 ? 4 : 0); e.z |= fb;
            blk[fb] = li; ready[fb] = j + LAG; kind[fb] = l2; accAt[j + LAG] = fb;
            if (li % BPG == BPG - 1) pubAt[li / BPG] = j + LAG;
            li++;
        } else if (l2next < P.nL2 && fb >= 0) {
            const int t = BPG + P.l2pos + l2next;
            e.x = enc_block(t) | (l2next == P.nL2 - 1 ? 4 : 0); e.z |= fb;
            blk[fb] = t; ready[fb] = j + LAG; kind[fb] = 2;
            l2next++;
        }
        if (accAt[j] >= 0) { e.z |= accAt[j] << 4 | 3u << 11; if (kind[accAt[j]] == 1) blk[accAt[j]] = -1; }
        {
            int eb = -1, mb = -1, best = -1;
            nfree = 0; fb = -1;
            for (int i = NRB - 1; i >= 0; i--) { if (reg[i] < 0) eb = i; else if (mb < 0 || reg[i] < reg[mb]) mb = i; }
            for (int k = NB - 1; k >= 0; k--) {
                if (blk[k] < 0) { nfree++; fb = k; }
                else if (ready[k] <= j && kind[k] == 0 && (best < 0 || blk[k] > blk[best])) best = k;
            }
            int sb = -1, sk = -1;
            if (li < NBLK && nfree == 0 && eb >= 0 && best >= 0) { sb = eb; sk = best; }
            else if (mb >= 0 && best >= 0 && reg[mb] / BPG < blk[best] / BPG) { sb = mb; sk = best; }
            else if (mb >= 0 && fb >= 0 && ((li >= NBLK && l2next >= P.nL2) ||
                                            (wmode && l2next >= P.nEarly && nfree + E - stored > LAG + 1 && reg[mb] / BPG < 2))) { sb = mb; sk = fb; }
            if (sb >= 0) {
                e.z |= 1u << 13 | sk << 16 | (sb * 2 + par[sb]) << 20;
                par[sb] ^= 1;
                const int tmp = reg[sb]; reg[sb] = blk[sk]; blk[sk] = tmp;
                ready[sk] = j; kind[sk] = 0;
            }
        }
        for (int g = 0; g < 3; g++) if (j == pubAt[g]) e.z |= 1u << 14 | g << 8;
        prog.e[j] = e;
    }
    prog.n = j;
    prog.e[j - 3].z |= 1u << 15;
    double credit = 0.999, t = 0;
    int want = 0;
    for (j = 0; j < prog.n; j++) {
        const int need = prog.e[j].y >> 8, before = want, start = pubAt[0] + P.dPoll;
        if (j >= start && mode[j] == 0 && want < E && want < P.wAt) {
            credit += j < start + P.absSteps ? (double)P.nAbs / P.absSteps : 1.0;
            if (credit > 1.999) credit = 1.999;
            if (credit >= 1.0 && avail[want] <= j) want++;
        }
        if (want < need) want = need;
        if (want > before) credit -= 1.0;
        prog.e[j].y |= want;
        prog.e[j].t = (uint32_t)(t * tscale);
        if (mode[j] == 1) t += P.tW + (want == E ? P.tWR : 0);
        else if (mode[j] != 3) t += j == 0 ? P.tFirst : mode[j] == 2 ? P.tL2 : want == 0 ? P.tL0 : P.tL;
        if (want > before && mode[j] != 1) {
            const double f = mode[j] == 3 ? (want - E - 1) / (double)P.nF : (want - P.n1) / (double)(P.n2 - P.n1);
            const double c = f < 0 ? 0 : f > 1 ? 1 : f;
            t += want >= NBLK - P.nZ ? P.tZ : want >= NBLK - P.nE ? P.tE : mode[j] == 3 ? P.tF1 + c * (P.tF2 - P.tF1) : P.tS1 + c * (P.tS2 - P.tS1);
        }
    }
    return prog.e[0].x == enc_block(0) && prog.e[0].z == 0;
}

static const Plan kPlan = {5,5,6,14,180,860,70,1630,4,20,720,720,8,836,12,103,740,2380,0,450,250,23,1100,3,8,740,450,930,846,2,450,1250,2};

constexpr int FB_BLOCKS = 1024;
__device__ float g_fb_part[FB_BLOCKS * C];
__device__ __nv_bfloat16 g_fb_s[C];
__global__ void fb_sum(const __nv_bfloat16* __restrict__ x, int rows) {
    for (int c = threadIdx.x; c < C; c += blockDim.x) {
        float a = 0.f;
        for (int r = blockIdx.x; r < rows; r += gridDim.x) a += __bfloat162float(x[(size_t)r * C + c]);
        g_fb_part[blockIdx.x * C + c] = a;
    }
}
__global__ void fb_gate(const __nv_bfloat16* __restrict__ w1d, int rows) {
    for (int c = threadIdx.x; c < C; c += blockDim.x) {
        float a = 0.f;
        for (int i = 0; i < FB_BLOCKS; i++) a += g_fb_part[i * C + c];
        g_fb_s[c] = gate(a, (float)rows, __bfloat162float(w1d[0]));
    }
}
__global__ void fb_scale(const __nv_bfloat16* __restrict__ x, __nv_bfloat16* __restrict__ out, size_t n) {
    for (size_t i = blockIdx.x * (size_t)blockDim.x + threadIdx.x; i < n; i += (size_t)gridDim.x * blockDim.x) out[i] = __hmul(x[i], g_fb_s[i % C]);
}

}

extern "C" void kernel_launch(void* const* d_in, const int* in_sizes, int n_in, void* d_out, int out_size) {
    using namespace eca;
    (void)n_in; (void)out_size;
    static int mode = -1;
    static Prog prog;
    if (mode < 0) {
        int dev = 0, sms = 0, occ = 0, coop = 0, khz = 0, bits = 0;
        cudaGetDevice(&dev);
        cudaDeviceGetAttribute(&sms, cudaDevAttrMultiProcessorCount, dev);
        cudaDeviceGetAttribute(&coop, cudaDevAttrCooperativeLaunch, dev);
        cudaDeviceGetAttribute(&khz, cudaDevAttrMemoryClockRate, dev);
        cudaDeviceGetAttribute(&bits, cudaDevAttrGlobalMemoryBusWidth, dev);
        double tscale = khz > 0 && bits > 0 ? 2619000.0 * 5120.0 / ((double)khz * bits) : 1.0;
        if (tscale < 0.5 || tscale > 2.0) tscale = 1.0;
        bool ok = cudaFuncSetAttribute(eca_kernel, cudaFuncAttributeMaxDynamicSharedMemorySize, SMEM_BYTES) == cudaSuccess;
        ok = ok && cudaOccupancyMaxActiveBlocksPerMultiprocessor(&occ, eca_kernel, 384, SMEM_BYTES) == cudaSuccess;
        ok = ok && coop && occ >= 1 && sms >= G && build_program(kPlan, prog, tscale);
        (void)cudaGetLastError();
        mode = ok ? 1 : 0;
    }
    const char* x = (const char*)d_in[0];
    const __nv_bfloat16* w = (const __nv_bfloat16*)d_in[1];
    char* out = (char*)d_out;
    if (mode == 1 && in_sizes[0] == HW * C && (((uintptr_t)x | (uintptr_t)out) & 15) == 0) {
        void* args[4] = {&x, &w, &out, &prog};
        cudaLaunchCooperativeKernel((const void*)eca_kernel, dim3(G), dim3(384), args, SMEM_BYTES, cudaStreamPerThread);
    } else {
        const int rows = in_sizes[0] / C;
        fb_sum<<<FB_BLOCKS, 384, 0, cudaStreamPerThread>>>((const __nv_bfloat16*)x, rows);
        fb_gate<<<1, 384, 0, cudaStreamPerThread>>>(w, rows);
        fb_scale<<<1024, 256, 0, cudaStreamPerThread>>>((const __nv_bfloat16*)x, (__nv_bfloat16*)out, (size_t)in_sizes[0]);
    }
}
```

```cpp
#include <cuda_runtime.h>
#include <cuda_bf16.h>
#include <stdint.h>
#include <string.h>

namespace eca {

constexpr int C = 384, HW = 384 * 384;
constexpr int G = 132;
constexpr int REP = 4;
constexpr int U = 4096;
constexpr int Q = 5;
constexpr int BLK = Q * U;
constexpr int NB = 11;
constexpr int NRB = 10;
constexpr int BPG = 14;
constexpr int NBLK = 3 * BPG;
constexpr int LAG = 2;
constexpr int NL1 = 2;
constexpr int MAXSTEP = 84;
constexpr int SHIFT_FRAC = 13;
constexpr uint32_t CSTEP = 2 * 768, KSTEP = G * CSTEP, WSTEP = Q * KSTEP, BSTEP = 8 * WSTEP;
constexpr uint32_t NBYTES = (uint32_t)HW * C * 2;
constexpr uint32_t SCR_OFF = NB * BLK, RED_OFF = SCR_OFF + 4096, SV_OFF = RED_OFF + 128, BAR_OFF = SV_OFF + 768, SMEM_BYTES = BAR_OFF + 128;
constexpr uint32_t BAR_PUB = BAR_OFF, BAR_DONE = BAR_PUB + 24, BAR_S = BAR_OFF + 32, BAR_STEP = BAR_OFF + 64, W_OFF = BAR_OFF + 96, LATE_OFF = BAR_OFF + 100, SHIFT_OFF = BAR_OFF + 112;

struct __align__(16) Step { uint32_t t, y, x, z; };
struct Prog { int n, stagger, xd0, xd1, xd2, xd3, theta, gain, tau, cap, pad1, pad2; Step e[MAXSTEP]; uint32_t st[48]; };

constexpr uint32_t PROW = (G + 4) * 8;
__device__ __align__(256) uint32_t g_part[48 * PROW];
__device__ __align__(256) uint32_t g_s[REP * 256];
__device__ __align__(256) unsigned g_shift[4];
__device__ __align__(256) unsigned g_arrive;

__device__ __forceinline__ uint32_t now_ns() { uint32_t t; asm volatile("mov.u32 %0, %globaltimer_lo;" : "=r"(t)); return t; }
__device__ __forceinline__ void mbar_init(uint32_t bar, uint32_t cnt) { asm volatile("mbarrier.init.shared::cta.b64 [%0], %1;" :: "r"(bar), "r"(cnt) : "memory"); }
__device__ __forceinline__ void mbar_arrive(uint32_t bar) { asm volatile("mbarrier.arrive.shared::cta.b64 _, [%0];" :: "r"(bar) : "memory"); }
__device__ __forceinline__ void mbar_wait(uint32_t bar, uint32_t parity) {
#pragma unroll 1
    for (int i = 0; i < (1 << 21); i++) {
        uint32_t ok;
        asm volatile("{\n.reg .pred p;\nmbarrier.try_wait.parity.shared::cta.b64 p, [%1], %2, 1000;\nselp.u32 %0, 1, 0, p;\n}"
                     : "=r"(ok) : "r"(bar), "r"(parity) : "memory");
        if (ok) return;
    }
}
__device__ __forceinline__ bool mbar_test(uint32_t bar) {
    uint32_t ok;
    asm volatile("{\n.reg .pred p;\nmbarrier.test_wait.parity.shared::cta.b64 p, [%1], 0;\nselp.u32 %0, 1, 0, p;\n}" : "=r"(ok) : "r"(bar) : "memory");
    return ok;
}
__device__ __forceinline__ void spin_ns(uint32_t ns) {
    const uint32_t a = now_ns();
#pragma unroll 1
    for (int it = 0; it < 256; it++) { if (now_ns() - a >= ns) break; __nanosleep(32); }
}
__device__ __forceinline__ uint32_t opaque(uint32_t a) { uint32_t t; asm volatile("max.u32 %0, %1, 16;" : "=r"(t) : "r"(a)); return t; }
__device__ __forceinline__ uint64_t policy_evict_first() { uint64_t p; asm volatile("createpolicy.fractional.L2::evict_first.b64 %0, 1.0;" : "=l"(p)); return p; }
__device__ __forceinline__ uint4 lds128(uint32_t a) { uint4 v; asm volatile("ld.volatile.shared.v4.u32 {%0,%1,%2,%3}, [%4];" : "=r"(v.x), "=r"(v.y), "=r"(v.z), "=r"(v.w) : "r"(a) : "memory"); return v; }
__device__ __forceinline__ void sts128(uint32_t a, uint4 v) { asm volatile("st.volatile.shared.v4.u32 [%0], {%1,%2,%3,%4};" :: "r"(a), "r"(v.x), "r"(v.y), "r"(v.z), "r"(v.w) : "memory"); }
__device__ __forceinline__ uint32_t lds32(uint32_t a) { uint32_t v; asm volatile("ld.volatile.shared.u32 %0, [%1];" : "=r"(v) : "r"(a) : "memory"); return v; }
__device__ __forceinline__ void sts32(uint32_t a, uint32_t v) { asm volatile("st.volatile.shared.u32 [%0], %1;" :: "r"(a), "r"(v) : "memory"); }
__device__ __forceinline__ uint32_t ld_relaxed(const void* p) { uint32_t v; asm volatile("ld.relaxed.gpu.global.u32 %0, [%1];" : "=r"(v) : "l"(p) : "memory"); return v; }
__device__ __forceinline__ void st_relaxed(void* p, uint32_t v) { asm volatile("st.relaxed.gpu.global.u32 [%0], %1;" :: "l"(p), "r"(v) : "memory"); }
__device__ __forceinline__ void accum(float* a, uint32_t addr) {
    uint32_t x, y; asm volatile("ld.volatile.shared.v2.u32 {%0,%1}, [%2];" : "=r"(x), "=r"(y) : "r"(addr) : "memory");
    a[0] += __uint_as_float(x << 16); a[1] += __uint_as_float(x & 0xffff0000u);
    a[2] += __uint_as_float(y << 16); a[3] += __uint_as_float(y & 0xffff0000u);
}
__device__ __forceinline__ uint32_t bmul2(uint32_t a, uint32_t b) { uint32_t d; asm("mul.rn.bf16x2 %0, %1, %2;" : "=r"(d) : "r"(a), "r"(b)); return d; }
__device__ __forceinline__ uint4 scale(uint4 v, uint4 s) { return make_uint4(bmul2(v.x, s.x), bmul2(v.y, s.y), bmul2(v.z, s.z), bmul2(v.w, s.w)); }
__device__ __forceinline__ float bf16r(float x) { return __bfloat162float(__float2bfloat16_rn(x)); }
__device__ __forceinline__ __nv_bfloat16 gate(float sum, float n, float w) {
    const float g = bf16r(__fdiv_rn(bf16r(sum), n));
    const float z = bf16r(g * w);
    return __float2bfloat16_rn(__frcp_rn(1.f + expf(-z)));
}
__device__ __forceinline__ uint32_t enc(float v) { return ~min(__float_as_uint(v), 0xFFFFFFFEu); }

__device__ __forceinline__ float dec(uint32_t u) { return __uint_as_float(~u); }

template <int LO, int HI> __device__ __forceinline__ void swap_block(uint4* r, int sel, uint32_t a) {
    if constexpr (HI - LO == 1) {
        uint4* v = r + (LO >> 1) * Q;
        const uint4 t = lds128(a);
        if constexpr ((LO & 1) == 0) {
#pragma unroll
            for (int k = 0; k < Q - 1; k++) { sts128(a + k * U, v[k]); v[k] = lds128(a + (k + 1) * U); }
            sts128(a + (Q - 1) * U, v[Q - 1]); v[Q - 1] = t;
        } else {
#pragma unroll
            for (int k = Q - 1; k > 0; k--) { sts128(a + ((k + 1) % Q) * U, v[k]); v[k] = lds128(a + k * U); }
            sts128(a + U, v[0]); v[0] = t;
        }
    } else {
        if (sel < (LO + HI) / 2) swap_block<LO, (LO + HI) / 2>(r, sel, a); else swap_block<(LO + HI) / 2, HI>(r, sel, a);
    }
}
template <int K> __device__ __forceinline__ void load_block(uint32_t sa, const char* src, uint32_t ga, uint64_t pol) {
    if constexpr (K < Q) {
        asm volatile("{\n.reg .pred p;\nsetp.ge.u32 p, %3, %6;\ncp.async.cg.shared.global.L2::cache_hint [%0+%4], [%1+%5], 16, p, %2;\n}"
                     :: "r"(sa), "l"(src), "l"(pol), "r"(ga), "n"(K * U), "n"(K * KSTEP), "n"(NBYTES - K * KSTEP) : "memory");
        load_block<K + 1>(sa, src, ga, pol);
    }
}
template <int K> __device__ __forceinline__ void load_block_l1(uint32_t sa, const char* src, uint32_t ga, uint64_t pol) {
    if constexpr (K < NL1) {
        asm volatile("cp.async.ca.shared.global.L2::cache_hint [%0+%3], [%1+%4], 16, %2;" :: "r"(sa), "l"(src), "l"(pol), "n"(K * U), "n"(K * KSTEP) : "memory");
        load_block_l1<K + 1>(sa, src, ga, pol);
    } else load_block<K>(sa, src, ga, pol);
}
template <int K> __device__ __forceinline__ void store_block(uint32_t sa, char* dst, uint32_t ga, uint4 s4, uint64_t pol) {
    if constexpr (K < Q) {
        const uint4 v = scale(lds128(sa + K * U), s4);
        asm volatile("{\n.reg .pred p;\nsetp.lt.u32 p, %6, %8;\n@p st.global.L1::no_allocate.L2::cache_hint.v4.u32 [%0+%7], {%1,%2,%3,%4}, %5;\n}"
                     :: "l"(dst), "r"(v.x), "r"(v.y), "r"(v.z), "r"(v.w), "l"(pol), "r"(ga), "n"(K * KSTEP), "n"(NBYTES - K * KSTEP) : "memory");
        store_block<K + 1>(sa, dst, ga, s4, pol);
    }
}

__global__ void __launch_bounds__(384, 1)
eca_kernel(const char* __restrict__ x, const __nv_bfloat16* __restrict__ w1d, char* __restrict__ out, const __grid_constant__ Prog S) {
    extern __shared__ __align__(1024) char smem[];
    const uint32_t tid = threadIdx.x, lane = tid & 31, warp = tid >> 5;
    const uint32_t b = blockIdx.x;
    const uint32_t s0 = (uint32_t)__cvta_generic_to_shared(smem);
    const uint32_t tstart = now_ns();
    const uint64_t pol = policy_evict_first();
    if (warp < 8) {
        load_block<0>(opaque(s0 + tid * 16), x + (b * CSTEP + warp * WSTEP + (lane >> 4) * 768 + (lane & 15) * 16), 0, pol);
        asm volatile("cp.async.commit_group;" ::: "memory");
    } else if (tid == 256) {
        for (int g = 0; g < 3; g++) { mbar_init(s0 + BAR_PUB + g * 8, 8); mbar_init(s0 + BAR_S + g * 8, 1); }
        mbar_init(s0 + BAR_STEP, 8); mbar_init(s0 + BAR_STEP + 8, 8); mbar_init(s0 + BAR_DONE, 8);
        sts32(s0 + SHIFT_OFF, 0); sts32(s0 + LATE_OFF, 0);
    }
    __syncthreads();

    if (warp >= 8) {
        asm volatile("setmaxnreg.dec.sync.aligned.u32 %0;" :: "n"(24));
        if (warp > 8 && ((const uint32_t*)S.e)[min(((lane & 7) * 3 + warp - 8) * 16, MAXSTEP * 4 + 47u)] == 0xffffffffu) sts32(s0 + LATE_OFF, 0);
        const uint32_t t = tid & 127;
        if (warp == 8) {
#pragma unroll
            for (int i = 0; i < 3; i++) *(uint4*)&g_part[(i * 16 + (lane & 15)) * PROW + b * 8 + (lane >> 4) * 4] = make_uint4(0, 0, 0, 0);
            if (b == 0 && lane == 0) g_shift[0] = 0;
            if (b < REP) { *(uint4*)&g_s[b * 256 + lane * 4] = make_uint4(0, 0, 0, 0); *(uint4*)&g_s[b * 256 + 128 + lane * 4] = make_uint4(0, 0, 0, 0); }
            __threadfence();
            __syncwarp();
            if (lane == 0) {
                const bool gen = atomicInc(&g_arrive, 2 * G - 1) >= G;
#pragma unroll 1
                for (int it = 0; it < (1 << 21); it++) {
                    spin_ns(it ? 500 : 2500);
                    if ((ld_relaxed(&g_arrive) >= G) != gen) break;
                }
                sts32(s0 + W_OFF, __float_as_uint(__bfloat162float(w1d[0])));
            }
            __syncwarp();
            __threadfence();
        }
        asm volatile("bar.sync 1, 128;" ::: "memory");
#pragma unroll 1
        for (uint32_t g = 0; g < 4; g++) {
            if (t == 32) {
#pragma unroll 1
                for (int it = 0; it < (1 << 20); it++) {
                    uint32_t late; asm volatile("atom.shared.exch.b32 %0, [%1], 0;" : "=r"(late) : "r"(s0 + LATE_OFF) : "memory");
                    const int ex = (int)(late - (lds32(s0 + SHIFT_OFF) >> SHIFT_FRAC)) - S.theta;
                    if (ex > 0) asm volatile("red.relaxed.gpu.global.add.u32 [%0], %1;" :: "l"(g_shift), "r"(min(ex, S.cap) * S.gain) : "memory");
                    asm volatile("cp.async.cg.shared.global [%0], [%1], 16;" :: "r"(s0 + SHIFT_OFF), "l"(g_shift) : "memory");
                    uint32_t ok;
                    asm volatile("{\n.reg .pred p;\nmbarrier.try_wait.parity.shared::cta.b64 p, [%1], 0, %2;\nselp.u32 %0, 1, 0, p;\n}"
                                 : "=r"(ok) : "r"(s0 + BAR_PUB + g * 8), "r"(S.tau) : "memory");
                    if (ok) break;
                }
                if (g == 3) asm volatile("cp.async.wait_all;" ::: "memory");
            }
            __syncwarp();
            if (g == 3) break;
            mbar_wait(s0 + BAR_PUB + g * 8, 0);
            {
                const uint32_t a = s0 + SCR_OFF + t * 4;
                float p[8];
#pragma unroll
                for (int i = 0; i < 8; i++) p[i] = __uint_as_float(lds32(a + i * 512));
                st_relaxed(&g_part[(g * 16 + (t >> 3)) * PROW + b * 8 + (t & 7)], enc(((p[0] + p[1]) + (p[2] + p[3])) + ((p[4] + p[5]) + (p[6] + p[7]))));
            }
            const bool reducer = (b & 7) == 0 && b < 128;
            if (reducer) {
                const uint32_t* src = &g_part[(g * 16 + (b >> 3)) * PROW + t];
                uint32_t p[9];
#pragma unroll 1
                for (int it = 0; it < (1 << 20); it++) {
                    spin_ns(it ? S.xd2 : S.xd0);
#pragma unroll
                    for (int i = 0; i < 8; i++) p[i] = ld_relaxed(src + i * 128);
                    p[8] = t < G * 8 - 1024 ? ld_relaxed(src + 1024) : ~0u;
                    const uint32_t mn = min(min(min(p[0], p[1]), min(p[2], p[3])), min(min(min(p[4], p[5]), min(p[6], p[7])), p[8]));
                    if (__all_sync(0xffffffffu, mn != 0)) break;
                }
                float v = (((dec(p[0]) + dec(p[1])) + (dec(p[2]) + dec(p[3]))) + ((dec(p[4]) + dec(p[5])) + (dec(p[6]) + dec(p[7])))) + dec(p[8]);
                v += __shfl_xor_sync(0xffffffffu, v, 8); v += __shfl_xor_sync(0xffffffffu, v, 16);
                if (lane < 8) sts32(s0 + RED_OFF + (t >> 5) * 32 + lane * 4, __float_as_uint(v));
            }
            asm volatile("bar.sync 1, 128;" ::: "memory");
            if (warp == 8) {
                if (reducer) {
                    const uint32_t a = s0 + RED_OFF + (lane & 7) * 4;
                    const float v = (__uint_as_float(lds32(a)) + __uint_as_float(lds32(a + 32))) + (__uint_as_float(lds32(a + 64)) + __uint_as_float(lds32(a + 96)));
                    const uint32_t hb = __bfloat16_as_ushort(gate(v, (float)HW, __uint_as_float(lds32(s0 + W_OFF)))) & 0x7fffu;
                    const uint32_t w2 = ~(hb | (__shfl_xor_sync(0xffffffffu, hb, 1) << 16));
                    if (!(lane & 1)) st_relaxed(&g_s[(t >> 3) * 256 + g * 64 + (b >> 3) * 4 + ((t & 7) >> 1)], w2);
                }
                spin_ns(reducer ? S.xd3 : S.xd1);
                uint32_t a0, a1;
#pragma unroll 1
                for (int it = 0; it < (1 << 21); it++) {
                    asm volatile("ld.relaxed.gpu.global.v2.u32 {%0,%1}, [%2];" : "=r"(a0), "=r"(a1) : "l"(&g_s[(b % REP) * 256 + g * 64 + t * 2]) : "memory");
                    if (__all_sync(0xffffffffu, a0 && a1)) break;
                    spin_ns(S.xd2);
                }
                asm volatile("st.shared.v2.u32 [%0], {%1,%2};" :: "r"(s0 + SV_OFF + g * 256 + lane * 8), "r"(~a0), "r"(~a1) : "memory");
                __syncwarp();
                if (lane == 0) mbar_arrive(s0 + BAR_S + g * 8);
            }
        }
    } else {
        asm volatile("setmaxnreg.inc.sync.aligned.u32 %0;" :: "n"(240));
        const uint32_t sbase = __shfl_sync(0xffffffffu, s0 + tid * 16, lane);
        auto fresh = [&]() { uint32_t o; asm volatile("mov.u32 %0, %1;" : "=r"(o) : "r"(sbase)); return o; };
        const uint32_t gcta = b * CSTEP - (s0 >> 9) * WSTEP;
        auto gaddr = [&](uint32_t off) { const uint32_t o = fresh(); return (o & 255) + (o & 256) * 3 + (o >> 9) * WSTEP + gcta + (off & ~127u); };
        float acc[4] = {0.f, 0.f, 0.f, 0.f};
        uint4 r[NRB * Q];
#pragma unroll
        for (int i = 0; i < NRB * Q; i++) asm volatile("" : "=r"(r[i].x), "=r"(r[i].y), "=r"(r[i].z), "=r"(r[i].w));
        uint4 s4 = make_uint4(0, 0, 0, 0);
        uint32_t js = 0;
#pragma unroll 1
        for (int j = 1; j < S.n; j++) {
            Step e;
            e.t = S.e[j].t; e.y = S.e[j].y;
            {
                const uint32_t tt = tstart + ((fresh() >> 9) - (s0 >> 9)) * S.stagger + e.t;
                const uint32_t now = now_ns();
                int d = (int)(tt + (lds32(s0 + SHIFT_OFF) >> SHIFT_FRAC) - now);
                asm volatile("{\n.reg .pred p;\nsetp.lt.s32 p, %2, 0;\n@p red.shared.max.u32 [%0], %1;\n}"
                             :: "r"(s0 + LATE_OFF), "r"(now - tt), "r"((sbase & 511) == 0 ? d : 0) : "memory");
#pragma unroll 1
                for (int it = 0; d > 0 && it < 4096; it++) { if (d > 100) __nanosleep(32); d = (int)(tt + (lds32(s0 + SHIFT_OFF) >> SHIFT_FRAC) - now_ns()); }
            }
            if (j >= 3) mbar_wait(s0 + BAR_STEP + (j & 1) * 8, ((j - 3) >> 1) & 1);
#pragma unroll 1
            for (bool opt = true; js < (opt ? (e.y & 255) : (e.y >> 8)); opt = false) {
                const uint32_t y = S.st[js];
                if (y & 8) {
                    const int g = (y >> 4) & 3;
                    if (js < (e.y >> 8)) mbar_wait(s0 + BAR_S + g * 8, 0);
                    else if (!mbar_test(s0 + BAR_S + g * 8)) break;
                    s4 = lds128(s0 + SV_OFF + g * 256 + (sbase & 255));
                }
                const uint32_t ga = gaddr(y & 0x0fffffffu);
                store_block<0>(sbase + (y >> 28) * BLK, out + ga, ga, s4, pol);
                js++;
            }
            { int jj; asm volatile("mov.u32 %0, %1;" : "=r"(jj) : "r"(j)); e.x = S.e[jj].x; e.z = S.e[jj].z; }
            if (e.x & 1) {
                const uint32_t ga = gaddr(e.x);
                const char* src = x + ga;
                if (e.x & 4) load_block_l1<0>(opaque(sbase + (e.z & 15) * BLK), src, ga, pol);
                else load_block<0>(opaque(sbase + (e.z & 15) * BLK), src, ga, pol);
                if ((e.x & 2) && (sbase & 127) == 0) {
#pragma unroll
                    for (int k = 0; k < Q; k++)
                        if (k >= NL1 || !(e.x & 4)) asm volatile("prefetch.global.L2 [%0];" :: "l"(src + k * KSTEP) : "memory");
                }
            }
            asm volatile("cp.async.commit_group;" ::: "memory");
            if (e.z & (1u << 11)) asm volatile("cp.async.wait_group %0;" :: "n"(LAG) : "memory");
            if (e.z & (1u << 12)) {
                const uint32_t o = fresh(), sa = (o & ~511u) + ((o & 511) >> 1) + ((e.z >> 4) & 15) * BLK;
                __syncwarp();
#pragma unroll
                for (int k = 0; k < Q; k++) { accum(acc, sa + k * U); accum(acc, sa + k * U + 256); }
                __syncwarp();
            }
            if (e.z & (1u << 14)) {
                const int g = (e.z >> 8) & 3;
                if (g) mbar_wait(s0 + BAR_S - 8 + g * 8, 0);
                sts128(sbase + SCR_OFF, make_uint4(__float_as_uint(acc[0]), __float_as_uint(acc[1]), __float_as_uint(acc[2]), __float_as_uint(acc[3])));
                __syncwarp();
                if ((sbase & 511) == 0) mbar_arrive(s0 + BAR_PUB + g * 8);
#pragma unroll
                for (int i = 0; i < 4; i++) acc[i] = 0.f;
            }
            if (e.z & (1u << 13)) swap_block<0, 2 * NRB>(r, e.z >> 20, sbase + ((e.z >> 16) & 15) * BLK);
            __syncwarp();
            if ((sbase & 511) == 0) {
                mbar_arrive(s0 + BAR_STEP + (j & 1) * 8);
                if (e.z & (1u << 15)) mbar_arrive(s0 + BAR_DONE);
            }
        }
    }
}

struct Plan {
    int nL2;
    int dPoll;
    int nAbs, absSteps;
    int tFirst, tL;
    int tS1, tS2, n1, n2;
    int tF1, tF2, nF;
    int tE, nE;
    int stagger;
    int xd0, xd1, xd2, xd3;
    int theta, gain, tau;
    int l2pos;
    int wAt, tW, tWR, tL2;
    int tL0;
    int nZ, tZ;
    int cap;
    int nEarly;
    int rot1, rot2;
};

static bool build_program(const Plan& P, Prog& prog, double tscale = 1.0) {
    auto row_of = [&](int t) { return (t % BPG + (t < BPG ? 0 : t < 2 * BPG ? P.rot1 : P.rot2)) % BPG; };
    auto enc_block = [&](int t) { return (uint32_t)row_of(t) * BSTEP + (3 - t / BPG) % 3 * 256 + 1; };
    for (int i = 0; i < P.nL2; i++) if (row_of(BPG + P.l2pos + i) == BPG - 1) return false;
    memset(&prog, 0, sizeof(prog));
    prog.stagger = (int)(P.stagger * tscale); prog.xd0 = P.xd0; prog.xd1 = P.xd1; prog.xd2 = P.xd2; prog.xd3 = P.xd3;
    prog.theta = P.theta; prog.gain = P.gain; prog.tau = P.tau; prog.cap = P.cap;
    int blk[NB], ready[NB], kind[NB], reg[NRB], par[NRB], accAt[MAXSTEP + LAG];
    for (int k = 0; k < NB; k++) { blk[k] = -1; ready[k] = 0; kind[k] = 0; }
    for (int k = 0; k < NRB; k++) { reg[k] = -1; par[k] = 0; }
    for (int k = 0; k < MAXSTEP + LAG; k++) accAt[k] = -1;
    int pubAt[4] = {1 << 20, 1 << 20, 1 << 20, 1 << 20}, remain[3] = {BPG, BPG, BPG};
    if (P.l2pos + P.nL2 >= BPG) return false;
    if (P.nEarly > P.nL2) return false;
    const int E = NBLK - NB - NRB - (P.nL2 - P.nEarly);
    int li = 0, l2next = 0, stored = 0, sg = -1;
    int avail[NBLK], mode[MAXSTEP];
    int j = 0;
    for (;; j++) {
        if (j >= MAXSTEP) return false;
        Step e = {0, 0, 0, 0};
        const bool readsDone = li >= NBLK;
        int nfree = 0, fb = -1;
        if (stored == NBLK) break;
        if ((sg < 0 || remain[sg] == 0) && j > pubAt[sg + 1]) sg++;
        for (int k = 0; k < NB; k++) nfree += blk[k] < 0;
        const bool wmode = !readsDone && stored >= P.wAt && stored < E && (nfree == 0 || stored > P.wAt);
        mode[j] = readsDone ? 3 : wmode ? 1 : (stored == E && E > P.wAt) ? 2 : 0;
        bool did = false;
        if ((readsDone || wmode || nfree == 0) && sg >= 0) {
            int best = -1;
            for (int k = 0; k < NB; k++)
                if (blk[k] >= 0 && blk[k] / BPG == sg && ready[k] < j && kind[k] != 1) {
                    if (best < 0 || (kind[k] == 2) < (kind[best] == 2) || ((kind[k] == 2) == (kind[best] == 2) && blk[k] < blk[best])) best = k;
                }
            if (best >= 0) {
                prog.st[stored] = (enc_block(blk[best]) & ~1u) | (remain[sg] == BPG ? 8 : 0) | sg << 4 | (uint32_t)best << 28;
                avail[stored] = ready[best] + 1 > pubAt[sg] + 1 ? ready[best] + 1 : pubAt[sg] + 1;
                bool waited = kind[best] != 2;
                for (int q = ready[best]; q < j; q++) waited |= prog.e[q].z >> 11 & 1;
                if (!waited) prog.e[j - 1].z |= 1u << 11;
                if (kind[best] == 2) avail[stored] = j;
                blk[best] = -1; remain[sg]--; stored++; did = true;
            }
        }
        e.y = stored << 8;
        for (int k = NB - 1; k >= 0; k--) if (blk[k] < 0) fb = k;
        if (wmode && (!did || l2next >= P.nEarly)) {
            if (!did) return false;
        } else if (!readsDone && !wmode) {
            if (fb < 0) return false;
            const bool l2 = (li >= BPG + P.l2pos && li < BPG + P.l2pos + P.nL2);
            e.x = enc_block(li) | (l2 ? 2 : 0) | (li == BPG + P.l2pos + P.nL2 - 1 ? 4 : 0); e.z |= fb;
            blk[fb] = li; ready[fb] = j + LAG; kind[fb] = l2; accAt[j + LAG] = fb;
            if (li % BPG == BPG - 1) pubAt[li / BPG] = j + LAG;
            li++;
        } else if (l2next < P.nL2 && fb >= 0) {
            const int t = BPG + P.l2pos + l2next;
            e.x = enc_block(t) | (l2next == P.nL2 - 1 ? 4 : 0); e.z |= fb;
            blk[fb] = t; ready[fb] = j + LAG; kind[fb] = 2;
            l2next++;
        }
        if (accAt[j] >= 0) { e.z |= accAt[j] << 4 | 3u << 11; if (kind[accAt[j]] == 1) blk[accAt[j]] = -1; }
        {
            int eb = -1, mb = -1, best = -1;
            nfree = 0; fb = -1;
            for (int i = NRB - 1; i >= 0; i--) { if (reg[i] < 0) eb = i; else if (mb < 0 || reg[i] < reg[mb]) mb = i; }
            for (int k = NB - 1; k >= 0; k--) {
                if (blk[k] < 0) { nfree++; fb = k; }
                else if (ready[k] <= j && kind[k] == 0 && (best < 0 || blk[k] > blk[best])) best = k;
            }
            int sb = -1, sk = -1;
            if (li < NBLK && nfree == 0 && eb >= 0 && best >= 0) { sb = eb; sk = best; }
            else if (mb >= 0 && best >= 0 && reg[mb] / BPG < blk[best] / BPG) { sb = mb; sk = best; }
            else if (mb >= 0 && fb >= 0 && ((li >= NBLK && l2next >= P.nL2) ||
                                            (wmode && l2next >= P.nEarly && nfree + E - stored > LAG + 1 && reg[mb] / BPG < 2))) { sb = mb; sk = fb; }
            if (sb >= 0) {
                e.z |= 1u << 13 | sk << 16 | (sb * 2 + par[sb]) << 20;
                par[sb] ^= 1;
                const int tmp = reg[sb]; reg[sb] = blk[sk]; blk[sk] = tmp;
                ready[sk] = j; kind[sk] = 0;
            }
        }
        for (int g = 0; g < 3; g++) if (j == pubAt[g]) e.z |= 1u << 14 | g << 8;
        prog.e[j] = e;
    }
    prog.n = j;
    prog.e[j - 3].z |= 1u << 15;
    double credit = 0.999, t = 0;
    int want = 0;
    for (j = 0; j < prog.n; j++) {
        const int need = prog.e[j].y >> 8, before = want, start = pubAt[0] + P.dPoll;
        if (j >= start && mode[j] == 0 && want < E && want < P.wAt) {
            credit += j < start + P.absSteps ? (double)P.nAbs / P.absSteps : 1.0;
            if (credit > 1.999) credit = 1.999;
            if (credit >= 1.0 && avail[want] <= j) want++;
        }
        if (want < need) want = need;
        if (want > before) credit -= 1.0;
        prog.e[j].y |= want;
        prog.e[j].t = (uint32_t)(t * tscale);
        if (mode[j] == 1) t += P.tW + (want == E ? P.tWR : 0);
        else if (mode[j] != 3) t += j == 0 ? P.tFirst : mode[j] == 2 ? P.tL2 : want == 0 ? P.tL0 : P.tL;
        if (want > before && mode[j] != 1) {
            const double f = mode[j] == 3 ? (want - E - 1) / (double)P.nF : (want - P.n1) / (double)(P.n2 - P.n1);
            const double c = f < 0 ? 0 : f > 1 ? 1 : f;
            t += want >= NBLK - P.nZ ? P.tZ : want >= NBLK - P.nE ? P.tE : mode[j] == 3 ? P.tF1 + c * (P.tF2 - P.tF1) : P.tS1 + c * (P.tS2 - P.tS1);
        }
    }
    return prog.e[0].x == enc_block(0) && prog.e[0].z == 0;
}

static const Plan kPlan = {5,5,6,14,150,849,102,1450,4,20,760,674,10,842,12,103,740,2522,0,600,250,23,1150,3,9,714,331,925,840,2,410,1732,2,1,4};

constexpr int FB_BLOCKS = 1024;
__device__ float g_fb_part[FB_BLOCKS * C];
__device__ __nv_bfloat16 g_fb_s[C];
__global__ void fb_sum(const __nv_bfloat16* __restrict__ x, int rows) {
    for (int c = threadIdx.x; c < C; c += blockDim.x) {
        float a = 0.f;
        for (int r = blockIdx.x; r < rows; r += gridDim.x) a += __bfloat162float(x[(size_t)r * C + c]);
        g_fb_part[blockIdx.x * C + c] = a;
    }
}
__global__ void fb_gate(const __nv_bfloat16* __restrict__ w1d, int rows) {
    for (int c = threadIdx.x; c < C; c += blockDim.x) {
        float a = 0.f;
        for (int i = 0; i < FB_BLOCKS; i++) a += g_fb_part[i * C + c];
        g_fb_s[c] = gate(a, (float)rows, __bfloat162float(w1d[0]));
    }
}
__global__ void fb_scale(const __nv_bfloat16* __restrict__ x, __nv_bfloat16* __restrict__ out, size_t n) {
    for (size_t i = blockIdx.x * (size_t)blockDim.x + threadIdx.x; i < n; i += (size_t)gridDim.x * blockDim.x) out[i] = __hmul(x[i], g_fb_s[i % C]);
}

}

extern "C" void kernel_launch(void* const* d_in, const int* in_sizes, int n_in, void* d_out, int out_size) {
    using namespace eca;
    (void)n_in; (void)out_size;
    static int mode = -1;
    static Prog prog;
    if (mode < 0) {
        int dev = 0, sms = 0, occ = 0, coop = 0, khz = 0, bits = 0;
        cudaGetDevice(&dev);
        cudaDeviceGetAttribute(&sms, cudaDevAttrMultiProcessorCount, dev);
        cudaDeviceGetAttribute(&coop, cudaDevAttrCooperativeLaunch, dev);
        cudaDeviceGetAttribute(&khz, cudaDevAttrMemoryClockRate, dev);
        cudaDeviceGetAttribute(&bits, cudaDevAttrGlobalMemoryBusWidth, dev);
        double tscale = khz > 0 && bits > 0 ? 2619000.0 * 5120.0 / ((double)khz * bits) : 1.0;
        if (tscale < 0.5 || tscale > 2.0) tscale = 1.0;
        bool ok = cudaFuncSetAttribute(eca_kernel, cudaFuncAttributeMaxDynamicSharedMemorySize, SMEM_BYTES) == cudaSuccess;
        ok = ok && cudaOccupancyMaxActiveBlocksPerMultiprocessor(&occ, eca_kernel, 384, SMEM_BYTES) == cudaSuccess;
        ok = ok && coop && occ >= 1 && sms >= G && build_program(kPlan, prog, tscale);
        (void)cudaGetLastError();
        mode = ok ? 1 : 0;
    }
    const char* x = (const char*)d_in[0];
    const __nv_bfloat16* w = (const __nv_bfloat16*)d_in[1];
    char* out = (char*)d_out;
    if (mode == 1 && in_sizes[0] == HW * C && (((uintptr_t)x | (uintptr_t)out) & 15) == 0) {
        void* args[4] = {&x, &w, &out, &prog};
        cudaLaunchCooperativeKernel((const void*)eca_kernel, dim3(G), dim3(384), args, SMEM_BYTES, cudaStreamPerThread);
    } else {
        const int rows = in_sizes[0] / C;
        fb_sum<<<FB_BLOCKS, 384, 0, cudaStreamPerThread>>>((const __nv_bfloat16*)x, rows);
        fb_gate<<<1, 384, 0, cudaStreamPerThread>>>(w, rows);
        fb_scale<<<1024, 256, 0, cudaStreamPerThread>>>((const __nv_bfloat16*)x, (__nv_bfloat16*)out, (size_t)in_sizes[0]);
    }
}
```

```cpp
#include <cuda_runtime.h>
#include <cuda_bf16.h>
#include <stdint.h>
#include <string.h>

namespace eca {

constexpr int C = 384, HW = 384 * 384;
constexpr int G = 132;
constexpr int REP = 4;
constexpr int U = 4096;
constexpr int Q = 5;
constexpr int BLK = Q * U;
constexpr int NB = 11;
constexpr int NRB = 10;
constexpr int BPG = 14;
constexpr int NBLK = 3 * BPG;
constexpr int LAG = 2;
constexpr int NL1 = 2;
constexpr int MAXSTEP = 84;
constexpr int SHIFT_FRAC = 13;
constexpr uint32_t CSTEP = 2 * 768, KSTEP = G * CSTEP, WSTEP = Q * KSTEP, BSTEP = 8 * WSTEP;
constexpr uint32_t NBYTES = (uint32_t)HW * C * 2;
constexpr uint32_t SCR_OFF = NB * BLK, RED_OFF = SCR_OFF + 4096, SV_OFF = RED_OFF + 128, BAR_OFF = SV_OFF + 768, SMEM_BYTES = BAR_OFF + 128;
constexpr uint32_t BAR_PUB = BAR_OFF, BAR_DONE = BAR_PUB + 24, BAR_S = BAR_OFF + 32, BAR_STEP = BAR_OFF + 64, W_OFF = BAR_OFF + 96, LATE_OFF = BAR_OFF + 100, SHIFT_OFF = BAR_OFF + 112;

struct __align__(16) Step { uint32_t t, y, x, z; };
struct Prog { uint32_t first; int n, stagger, xd0, xd1, xd2, xd3, theta, gain, tau, cap, pad; Step e[MAXSTEP]; uint32_t st[48]; };

constexpr uint32_t PROW = (G + 4) * 8;
__device__ __align__(256) uint32_t g_part[48 * PROW];
__device__ __align__(256) uint32_t g_s[REP * 256];
__device__ __align__(256) unsigned g_shift[8];
__device__ __align__(256) unsigned g_arrive;

__device__ __forceinline__ uint32_t now_ns() { uint32_t t; asm volatile("mov.u32 %0, %globaltimer_lo;" : "=r"(t)); return t; }
__device__ __forceinline__ void mbar_init(uint32_t bar, uint32_t cnt) { asm volatile("mbarrier.init.shared::cta.b64 [%0], %1;" :: "r"(bar), "r"(cnt) : "memory"); }
__device__ __forceinline__ void mbar_arrive(uint32_t bar) { asm volatile("mbarrier.arrive.shared::cta.b64 _, [%0];" :: "r"(bar) : "memory"); }
__device__ __forceinline__ void mbar_wait(uint32_t bar, uint32_t parity) {
#pragma unroll 1
    for (int i = 0; i < (1 << 21); i++) {
        uint32_t ok;
        asm volatile("{\n.reg .pred p;\nmbarrier.try_wait.parity.shared::cta.b64 p, [%1], %2, 1000;\nselp.u32 %0, 1, 0, p;\n}"
                     : "=r"(ok) : "r"(bar), "r"(parity) : "memory");
        if (ok) return;
    }
}
__device__ __forceinline__ bool mbar_test(uint32_t bar) {
    uint32_t ok;
    asm volatile("{\n.reg .pred p;\nmbarrier.test_wait.parity.shared::cta.b64 p, [%1], 0;\nselp.u32 %0, 1, 0, p;\n}" : "=r"(ok) : "r"(bar) : "memory");
    return ok;
}
__device__ __forceinline__ void spin_ns(uint32_t ns) {
    const uint32_t a = now_ns();
#pragma unroll 1
    for (int it = 0; it < 256; it++) { if (now_ns() - a >= ns) break; __nanosleep(32); }
}
__device__ __forceinline__ uint32_t opaque(uint32_t a) { uint32_t t; asm volatile("max.u32 %0, %1, 16;" : "=r"(t) : "r"(a)); return t; }
__device__ __forceinline__ uint64_t policy_evict_first() { uint64_t p; asm volatile("createpolicy.fractional.L2::evict_first.b64 %0, 1.0;" : "=l"(p)); return p; }
__device__ __forceinline__ uint4 lds128(uint32_t a) { uint4 v; asm volatile("ld.volatile.shared.v4.u32 {%0,%1,%2,%3}, [%4];" : "=r"(v.x), "=r"(v.y), "=r"(v.z), "=r"(v.w) : "r"(a) : "memory"); return v; }
__device__ __forceinline__ void sts128(uint32_t a, uint4 v) { asm volatile("st.volatile.shared.v4.u32 [%0], {%1,%2,%3,%4};" :: "r"(a), "r"(v.x), "r"(v.y), "r"(v.z), "r"(v.w) : "memory"); }
__device__ __forceinline__ uint32_t lds32(uint32_t a) { uint32_t v; asm volatile("ld.volatile.shared.u32 %0, [%1];" : "=r"(v) : "r"(a) : "memory"); return v; }
__device__ __forceinline__ void sts32(uint32_t a, uint32_t v) { asm volatile("st.volatile.shared.u32 [%0], %1;" :: "r"(a), "r"(v) : "memory"); }
__device__ __forceinline__ uint32_t ld_relaxed(const void* p) { uint32_t v; asm volatile("ld.relaxed.gpu.global.u32 %0, [%1];" : "=r"(v) : "l"(p) : "memory"); return v; }
__device__ __forceinline__ void st_relaxed(void* p, uint32_t v) { asm volatile("st.relaxed.gpu.global.u32 [%0], %1;" :: "l"(p), "r"(v) : "memory"); }
__device__ __forceinline__ void accum(float* a, uint32_t addr) {
    uint32_t x, y; asm volatile("ld.volatile.shared.v2.u32 {%0,%1}, [%2];" : "=r"(x), "=r"(y) : "r"(addr) : "memory");
    a[0] += __uint_as_float(x << 16); a[1] += __uint_as_float(x & 0xffff0000u);
    a[2] += __uint_as_float(y << 16); a[3] += __uint_as_float(y & 0xffff0000u);
}
__device__ __forceinline__ uint32_t bmul2(uint32_t a, uint32_t b) { uint32_t d; asm("mul.rn.bf16x2 %0, %1, %2;" : "=r"(d) : "r"(a), "r"(b)); return d; }
__device__ __forceinline__ uint4 scale(uint4 v, uint4 s) { return make_uint4(bmul2(v.x, s.x), bmul2(v.y, s.y), bmul2(v.z, s.z), bmul2(v.w, s.w)); }
__device__ __forceinline__ float bf16r(float x) { return __bfloat162float(__float2bfloat16_rn(x)); }
__device__ __forceinline__ __nv_bfloat16 gate(float sum, float n, float w) {
    const float g = bf16r(__fdiv_rn(bf16r(sum), n));
    const float z = bf16r(g * w);
    return __float2bfloat16_rn(__frcp_rn(1.f + expf(-z)));
}
__device__ __forceinline__ uint32_t enc(float v) { return ~min(__float_as_uint(v), 0xFFFFFFFEu); }

__device__ __forceinline__ float dec(uint32_t u) { return __uint_as_float(~u); }

template <int LO, int HI> __device__ __forceinline__ void swap_block(uint4* r, int sel, uint32_t a) {
    if constexpr (HI - LO == 1) {
        uint4* v = r + (LO >> 1) * Q;
        const uint4 t = lds128(a);
        if constexpr ((LO & 1) == 0) {
#pragma unroll
            for (int k = 0; k < Q - 1; k++) { sts128(a + k * U, v[k]); v[k] = lds128(a + (k + 1) * U); }
            sts128(a + (Q - 1) * U, v[Q - 1]); v[Q - 1] = t;
        } else {
#pragma unroll
            for (int k = Q - 1; k > 0; k--) { sts128(a + ((k + 1) % Q) * U, v[k]); v[k] = lds128(a + k * U); }
            sts128(a + U, v[0]); v[0] = t;
        }
    } else {
        if (sel < (LO + HI) / 2) swap_block<LO, (LO + HI) / 2>(r, sel, a); else swap_block<(LO + HI) / 2, HI>(r, sel, a);
    }
}
template <int K> __device__ __forceinline__ void load_block(uint32_t sa, const char* src, uint32_t ga, uint64_t pol) {
    if constexpr (K < Q) {
        asm volatile("{\n.reg .pred p;\nsetp.ge.u32 p, %3, %6;\ncp.async.cg.shared.global.L2::cache_hint [%0+%4], [%1+%5], 16, p, %2;\n}"
                     :: "r"(sa), "l"(src), "l"(pol), "r"(ga), "n"(K * U), "n"(K * KSTEP), "n"(NBYTES - K * KSTEP) : "memory");
        load_block<K + 1>(sa, src, ga, pol);
    }
}
template <int K> __device__ __forceinline__ void load_block_l1(uint32_t sa, const char* src, uint32_t ga, uint64_t pol) {
    if constexpr (K < NL1) {
        asm volatile("cp.async.ca.shared.global.L2::cache_hint [%0+%3], [%1+%4], 16, %2;" :: "r"(sa), "l"(src), "l"(pol), "n"(K * U), "n"(K * KSTEP) : "memory");
        load_block_l1<K + 1>(sa, src, ga, pol);
    } else load_block<K>(sa, src, ga, pol);
}
template <int K> __device__ __forceinline__ void store_block(uint32_t sa, char* dst, uint32_t ga, uint4 s4, uint64_t pol) {
    if constexpr (K < Q) {
        const uint4 v = scale(lds128(sa + K * U), s4);
        asm volatile("{\n.reg .pred p;\nsetp.lt.u32 p, %6, %8;\n@p st.global.L1::no_allocate.L2::cache_hint.v4.u32 [%0+%7], {%1,%2,%3,%4}, %5;\n}"
                     :: "l"(dst), "r"(v.x), "r"(v.y), "r"(v.z), "r"(v.w), "l"(pol), "r"(ga), "n"(K * KSTEP), "n"(NBYTES - K * KSTEP) : "memory");
        store_block<K + 1>(sa, dst, ga, s4, pol);
    }
}

__global__ void __launch_bounds__(384, 1)
eca_kernel(const char* __restrict__ x, const __nv_bfloat16* __restrict__ w1d, char* __restrict__ out, const __grid_constant__ Prog S) {
    extern __shared__ __align__(1024) char smem[];
    const uint32_t tid = threadIdx.x, lane = tid & 31, warp = tid >> 5;
    const uint32_t b = blockIdx.x;
    const uint32_t s0 = (uint32_t)__cvta_generic_to_shared(smem);
    const uint32_t tstart = now_ns();
    const uint64_t pol = policy_evict_first();
    if (warp < 8) {
        load_block<0>(opaque(s0 + tid * 16), x + (S.first + b * CSTEP + warp * WSTEP + (lane >> 4) * 768 + (lane & 15) * 16), 0, pol);
        asm volatile("cp.async.commit_group;" ::: "memory");
    } else if (tid == 256) {
        for (int g = 0; g < 3; g++) { mbar_init(s0 + BAR_PUB + g * 8, 8); mbar_init(s0 + BAR_S + g * 8, 1); }
        mbar_init(s0 + BAR_STEP, 8); mbar_init(s0 + BAR_STEP + 8, 8); mbar_init(s0 + BAR_DONE, 8);
        sts32(s0 + SHIFT_OFF, 0); sts32(s0 + LATE_OFF, 0);
    }
    __syncthreads();

    if (warp >= 8) {
        asm volatile("setmaxnreg.dec.sync.aligned.u32 %0;" :: "n"(24));
        if (warp > 8 && ((const uint32_t*)S.e)[min(((lane & 7) * 3 + warp - 8) * 16, MAXSTEP * 4 + 47u)] == 0xffffffffu) sts32(s0 + LATE_OFF, 0);
        const uint32_t t = tid & 127;
        if (warp == 8) {
#pragma unroll
            for (int i = 0; i < 3; i++) *(uint4*)&g_part[(i * 16 + (lane & 15)) * PROW + b * 8 + (lane >> 4) * 4] = make_uint4(0, 0, 0, 0);
            if (b == 0 && lane < 2) *(uint4*)&g_shift[lane * 4] = make_uint4(0, 0, 0, 0);
            if (b < REP) { *(uint4*)&g_s[b * 256 + lane * 4] = make_uint4(0, 0, 0, 0); *(uint4*)&g_s[b * 256 + 128 + lane * 4] = make_uint4(0, 0, 0, 0); }
            __threadfence();
            __syncwarp();
            if (lane == 0) {
                const bool gen = atomicInc(&g_arrive, 2 * G - 1) >= G;
#pragma unroll 1
                for (int it = 0; it < (1 << 21); it++) {
                    spin_ns(it ? 500 : 2500);
                    if ((ld_relaxed(&g_arrive) >= G) != gen) break;
                }
                sts32(s0 + W_OFF, __float_as_uint(__bfloat162float(w1d[0])));
            }
            __syncwarp();
            __threadfence();
        }
        asm volatile("bar.sync 1, 128;" ::: "memory");
#pragma unroll 1
        for (uint32_t g = 0; g < 4; g++) {
            if (t == 32) {
#pragma unroll 1
                for (int it = 0; it < (1 << 20); it++) {
                    uint32_t late; asm volatile("atom.shared.exch.b32 %0, [%1], 0;" : "=r"(late) : "r"(s0 + LATE_OFF) : "memory");
                    const int ex = (int)(late - (lds32(s0 + SHIFT_OFF) >> SHIFT_FRAC)) - S.theta;
                    if (ex > 0) asm volatile("red.relaxed.gpu.global.add.u32 [%0], %1;" :: "l"(g_shift), "r"(min(ex, S.cap) * S.gain) : "memory");
                    asm volatile("cp.async.cg.shared.global [%0], [%1], 16;" :: "r"(s0 + SHIFT_OFF), "l"(g_shift) : "memory");
                    uint32_t ok;
                    asm volatile("{\n.reg .pred p;\nmbarrier.try_wait.parity.shared::cta.b64 p, [%1], 0, %2;\nselp.u32 %0, 1, 0, p;\n}"
                                 : "=r"(ok) : "r"(s0 + BAR_PUB + g * 8), "r"(S.tau) : "memory");
                    if (ok) break;
                }
                if (g == 3) asm volatile("cp.async.wait_all;" ::: "memory");
            }
            __syncwarp();
            if (g == 3) break;
            mbar_wait(s0 + BAR_PUB + g * 8, 0);
            {
                const uint32_t a = s0 + SCR_OFF + t * 4;
                float p[8];
#pragma unroll
                for (int i = 0; i < 8; i++) p[i] = __uint_as_float(lds32(a + i * 512));
                st_relaxed(&g_part[(g * 16 + (t >> 3)) * PROW + b * 8 + (t & 7)], enc(((p[0] + p[1]) + (p[2] + p[3])) + ((p[4] + p[5]) + (p[6] + p[7]))));
            }
            const bool reducer = (b & 7) == 0 && b < 128;
            if (reducer) {
                const uint32_t* src = &g_part[(g * 16 + (b >> 3)) * PROW + t];
                uint32_t p[9];
#pragma unroll 1
                for (int it = 0; it < (1 << 20); it++) {
                    spin_ns(it ? S.xd2 : S.xd0);
#pragma unroll
                    for (int i = 0; i < 8; i++) p[i] = ld_relaxed(src + i * 128);
                    p[8] = t < G * 8 - 1024 ? ld_relaxed(src + 1024) : ~0u;
                    const uint32_t mn = min(min(min(p[0], p[1]), min(p[2], p[3])), min(min(min(p[4], p[5]), min(p[6], p[7])), p[8]));
                    if (__all_sync(0xffffffffu, mn != 0)) break;
                }
                float v = (((dec(p[0]) + dec(p[1])) + (dec(p[2]) + dec(p[3]))) + ((dec(p[4]) + dec(p[5])) + (dec(p[6]) + dec(p[7])))) + dec(p[8]);
                v += __shfl_xor_sync(0xffffffffu, v, 8); v += __shfl_xor_sync(0xffffffffu, v, 16);
                if (lane < 8) sts32(s0 + RED_OFF + (t >> 5) * 32 + lane * 4, __float_as_uint(v));
            }
            asm volatile("bar.sync 1, 128;" ::: "memory");
            if (warp == 8) {
                if (reducer) {
                    const uint32_t a = s0 + RED_OFF + (lane & 7) * 4;
                    const float v = (__uint_as_float(lds32(a)) + __uint_as_float(lds32(a + 32))) + (__uint_as_float(lds32(a + 64)) + __uint_as_float(lds32(a + 96)));
                    const uint32_t hb = __bfloat16_as_ushort(gate(v, (float)HW, __uint_as_float(lds32(s0 + W_OFF)))) & 0x7fffu;
                    const uint32_t w2 = ~(hb | (__shfl_xor_sync(0xffffffffu, hb, 1) << 16));
                    if (!(lane & 1)) st_relaxed(&g_s[(t >> 3) * 256 + g * 64 + (b >> 3) * 4 + ((t & 7) >> 1)], w2);
                }
                spin_ns(reducer ? S.xd3 : S.xd1);
                uint32_t a0, a1;
#pragma unroll 1
                for (int it = 0; it < (1 << 21); it++) {
                    asm volatile("ld.relaxed.gpu.global.v2.u32 {%0,%1}, [%2];" : "=r"(a0), "=r"(a1) : "l"(&g_s[(b % REP) * 256 + g * 64 + t * 2]) : "memory");
                    if (__all_sync(0xffffffffu, a0 && a1)) break;
                    spin_ns(S.xd2);
                }
                asm volatile("st.shared.v2.u32 [%0], {%1,%2};" :: "r"(s0 + SV_OFF + g * 256 + lane * 8), "r"(~a0), "r"(~a1) : "memory");
                __syncwarp();
                if (lane == 0) mbar_arrive(s0 + BAR_S + g * 8);
            }
        }
    } else {
        asm volatile("setmaxnreg.inc.sync.aligned.u32 %0;" :: "n"(240));
        const uint32_t sbase = __shfl_sync(0xffffffffu, s0 + tid * 16, lane);
        auto fresh = [&]() { uint32_t o; asm volatile("mov.u32 %0, %1;" : "=r"(o) : "r"(sbase)); return o; };
        const uint32_t gcta = b * CSTEP - (s0 >> 9) * WSTEP;
        auto gaddr = [&](uint32_t off) { const uint32_t o = fresh(); return (o & 255) + (o & 256) * 3 + (o >> 9) * WSTEP + gcta + (off & ~127u); };
        float acc[4] = {0.f, 0.f, 0.f, 0.f};
        uint4 r[NRB * Q];
#pragma unroll
        for (int i = 0; i < NRB * Q; i++) asm volatile("" : "=r"(r[i].x), "=r"(r[i].y), "=r"(r[i].z), "=r"(r[i].w));
        uint4 s4 = make_uint4(0, 0, 0, 0);
        uint32_t js = 0;
#pragma unroll 1
        for (int j = 1; j < S.n; j++) {
            Step e;
            e.t = S.e[j].t; e.y = S.e[j].y;
            {
                const uint32_t tt = tstart + ((fresh() >> 9) - (s0 >> 9)) * S.stagger + e.t;
                const uint32_t now = now_ns();
                int d = (int)(tt + (lds32(s0 + SHIFT_OFF) >> SHIFT_FRAC) - now);
                asm volatile("{\n.reg .pred p;\nsetp.lt.s32 p, %2, 0;\n@p red.shared.max.u32 [%0], %1;\n}"
                             :: "r"(s0 + LATE_OFF), "r"(now - tt), "r"((sbase & 511) == 0 ? d : 0) : "memory");
#pragma unroll 1
                for (int it = 0; d > 0 && it < 4096; it++) { if (d > 100) __nanosleep(32); d = (int)(tt + (lds32(s0 + SHIFT_OFF) >> SHIFT_FRAC) - now_ns()); }
            }
            if (j >= 3) mbar_wait(s0 + BAR_STEP + (j & 1) * 8, ((j - 3) >> 1) & 1);
#pragma unroll 1
            for (bool opt = true; js < (opt ? (e.y & 255) : (e.y >> 8)); opt = false) {
                const uint32_t y = S.st[js];
                if (y & 8) {
                    const int g = (y >> 4) & 3;
                    if (js < (e.y >> 8)) mbar_wait(s0 + BAR_S + g * 8, 0);
                    else if (!mbar_test(s0 + BAR_S + g * 8)) break;
                    s4 = lds128(s0 + SV_OFF + g * 256 + (sbase & 255));
                }
                const uint32_t ga = gaddr(y & 0x0fffffffu);
                store_block<0>(sbase + (y >> 28) * BLK, out + ga, ga, s4, pol);
                js++;
            }
            { int jj; asm volatile("mov.u32 %0, %1;" : "=r"(jj) : "r"(j)); e.x = S.e[jj].x; e.z = S.e[jj].z; }
            if (e.x & 1) {
                const uint32_t ga = gaddr(e.x);
                const char* src = x + ga;
                if (e.x & 4) load_block_l1<0>(opaque(sbase + (e.z & 15) * BLK), src, ga, pol);
                else load_block<0>(opaque(sbase + (e.z & 15) * BLK), src, ga, pol);
                if ((e.x & 2) && (sbase & 127) == 0) {
#pragma unroll
                    for (int k = 0; k < Q; k++)
                        if (k >= NL1 || !(e.x & 4)) asm volatile("prefetch.global.L2 [%0];" :: "l"(src + k * KSTEP) : "memory");
                }
            }
            asm volatile("cp.async.commit_group;" ::: "memory");
            if (e.z & (1u << 11)) asm volatile("cp.async.wait_group %0;" :: "n"(LAG) : "memory");
            if (e.z & (1u << 12)) {
                const uint32_t o = fresh(), sa = (o & ~511u) + ((o & 511) >> 1) + ((e.z >> 4) & 15) * BLK;
                __syncwarp();
#pragma unroll
                for (int k = 0; k < Q; k++) { accum(acc, sa + k * U); accum(acc, sa + k * U + 256); }
                __syncwarp();
            }
            if (e.z & (1u << 14)) {
                const int g = (e.z >> 8) & 3;
                if (g) mbar_wait(s0 + BAR_S - 8 + g * 8, 0);
                sts128(sbase + SCR_OFF, make_uint4(__float_as_uint(acc[0]), __float_as_uint(acc[1]), __float_as_uint(acc[2]), __float_as_uint(acc[3])));
                __syncwarp();
                if ((sbase & 511) == 0) mbar_arrive(s0 + BAR_PUB + g * 8);
#pragma unroll
                for (int i = 0; i < 4; i++) acc[i] = 0.f;
            }
            if (e.z & (1u << 13)) swap_block<0, 2 * NRB>(r, e.z >> 20, sbase + ((e.z >> 16) & 15) * BLK);
            __syncwarp();
            if ((sbase & 511) == 0) {
                mbar_arrive(s0 + BAR_STEP + (j & 1) * 8);
                if (e.z & (1u << 15)) mbar_arrive(s0 + BAR_DONE);
            }
        }
    }
}

struct Plan {
    int nL2;
    int dPoll;
    int nAbs, absSteps;
    int tFirst, tL;
    int tS1, tS2, n1, n2;
    int tF1, tF2, nF;
    int tE, nE;
    int stagger;
    int xd0, xd1, xd2, xd3;
    int theta, gain, tau;
    int l2pos;
    int wAt, tW, tWR, tL2;
    int tL0;
    int nZ, tZ;
    int cap;
    int nEarly;
    int chunk[3];
    int row[NBLK];
};

static bool build_program(const Plan& P, Prog& prog, double tscale = 1.0) {
    auto enc_block = [&](int t) { return (uint32_t)P.row[t] * BSTEP + P.chunk[t / BPG] * 256 + 1; };
    if (P.l2pos + P.nL2 >= BPG || P.nEarly > P.nL2 || P.row[0] == BPG - 1) return false;
    for (int i = 0; i < P.nL2; i++) if (P.row[BPG + P.l2pos + i] == BPG - 1) return false;
    memset(&prog, 0, sizeof(prog));
    prog.first = enc_block(0) & ~127u;
    prog.stagger = (int)(P.stagger * tscale); prog.xd0 = P.xd0; prog.xd1 = P.xd1; prog.xd2 = P.xd2; prog.xd3 = P.xd3;
    prog.theta = P.theta; prog.gain = P.gain; prog.tau = P.tau; prog.cap = P.cap;
    int blk[NB], ready[NB], kind[NB], reg[NRB], par[NRB], accAt[MAXSTEP + LAG];
    for (int k = 0; k < NB; k++) { blk[k] = -1; ready[k] = 0; kind[k] = 0; }
    for (int k = 0; k < NRB; k++) { reg[k] = -1; par[k] = 0; }
    for (int k = 0; k < MAXSTEP + LAG; k++) accAt[k] = -1;
    int pubAt[4] = {1 << 20, 1 << 20, 1 << 20, 1 << 20}, remain[3] = {BPG, BPG, BPG};
    const int E = NBLK - NB - NRB - (P.nL2 - P.nEarly);
    int li = 0, l2next = 0, stored = 0, sg = -1;
    int avail[NBLK], mode[MAXSTEP];
    int j = 0;
    for (;; j++) {
        if (j >= MAXSTEP) return false;
        Step e = {0, 0, 0, 0};
        const bool readsDone = li >= NBLK;
        int nfree = 0, fb = -1;
        if (stored == NBLK) break;
        if ((sg < 0 || remain[sg] == 0) && j > pubAt[sg + 1]) sg++;
        for (int k = 0; k < NB; k++) nfree += blk[k] < 0;
        const bool wmode = !readsDone && stored >= P.wAt && stored < E && (nfree == 0 || stored > P.wAt);
        mode[j] = readsDone ? 3 : wmode ? 1 : (stored == E && E > P.wAt) ? 2 : 0;
        bool did = false;
        if ((readsDone || wmode || nfree == 0) && sg >= 0) {
            int best = -1;
            for (int k = 0; k < NB; k++)
                if (blk[k] >= 0 && blk[k] / BPG == sg && ready[k] < j && kind[k] != 1) {
                    if (best < 0 || (kind[k] == 2) < (kind[best] == 2) || ((kind[k] == 2) == (kind[best] == 2) && blk[k] < blk[best])) best = k;
                }
            if (best >= 0) {
                prog.st[stored] = (enc_block(blk[best]) & ~1u) | (remain[sg] == BPG ? 8 : 0) | sg << 4 | (uint32_t)best << 28;
                avail[stored] = ready[best] + 1 > pubAt[sg] + 1 ? ready[best] + 1 : pubAt[sg] + 1;
                bool waited = kind[best] != 2;
                for (int q = ready[best]; q < j; q++) waited |= prog.e[q].z >> 11 & 1;
                if (!waited) prog.e[j - 1].z |= 1u << 11;
                if (kind[best] == 2) avail[stored] = j;
                blk[best] = -1; remain[sg]--; stored++; did = true;
            }
        }
        e.y = stored << 8;
        for (int k = NB - 1; k >= 0; k--) if (blk[k] < 0) fb = k;
        if (wmode && (!did || l2next >= P.nEarly)) {
            if (!did) return false;
        } else if (!readsDone && !wmode) {
            if (fb < 0) return false;
            const bool l2 = (li >= BPG + P.l2pos && li < BPG + P.l2pos + P.nL2);
            e.x = enc_block(li) | (l2 ? 2 : 0) | (li == BPG + P.l2pos + P.nL2 - 1 ? 4 : 0); e.z |= fb;
            blk[fb] = li; ready[fb] = j + LAG; kind[fb] = l2; accAt[j + LAG] = fb;
            if (li % BPG == BPG - 1) pubAt[li / BPG] = j + LAG;
            li++;
        } else if (l2next < P.nL2 && fb >= 0) {
            const int t = BPG + P.l2pos + l2next;
            e.x = enc_block(t) | (l2next == P.nL2 - 1 ? 4 : 0); e.z |= fb;
            blk[fb] = t; ready[fb] = j + LAG; kind[fb] = 2;
            l2next++;
        }
        if (accAt[j] >= 0) { e.z |= accAt[j] << 4 | 3u << 11; if (kind[accAt[j]] == 1) blk[accAt[j]] = -1; }
        {
            int eb = -1, mb = -1, best = -1;
            nfree = 0; fb = -1;
            for (int i = NRB - 1; i >= 0; i--) { if (reg[i] < 0) eb = i; else if (mb < 0 || reg[i] < reg[mb]) mb = i; }
            for (int k = NB - 1; k >= 0; k--) {
                if (blk[k] < 0) { nfree++; fb = k; }
                else if (ready[k] <= j && kind[k] == 0 && (best < 0 || blk[k] > blk[best])) best = k;
            }
            int sb = -1, sk = -1;
            if (li < NBLK && nfree == 0 && eb >= 0 && best >= 0) { sb = eb; sk = best; }
            else if (mb >= 0 && best >= 0 && reg[mb] / BPG < blk[best] / BPG) { sb = mb; sk = best; }
            else if (mb >= 0 && fb >= 0 && ((li >= NBLK && l2next >= P.nL2) ||
                                            (wmode && l2next >= P.nEarly && nfree + E - stored > LAG + 1 && reg[mb] / BPG < 2))) { sb = mb; sk = fb; }
            if (sb >= 0) {
                e.z |= 1u << 13 | sk << 16 | (sb * 2 + par[sb]) << 20;
                par[sb] ^= 1;
                const int tmp = reg[sb]; reg[sb] = blk[sk]; blk[sk] = tmp;
                ready[sk] = j; kind[sk] = 0;
            }
        }
        for (int g = 0; g < 3; g++) if (j == pubAt[g]) e.z |= 1u << 14 | g << 8;
        prog.e[j] = e;
    }
    prog.n = j;
    prog.e[j - 3].z |= 1u << 15;
    double credit = 0.999, t = 0;
    int want = 0;
    for (j = 0; j < prog.n; j++) {
        const int need = prog.e[j].y >> 8, before = want, start = pubAt[0] + P.dPoll;
        if (j >= start && mode[j] == 0 && want < E && want < P.wAt) {
            credit += j < start + P.absSteps ? (double)P.nAbs / P.absSteps : 1.0;
            if (credit > 1.999) credit = 1.999;
            if (credit >= 1.0 && avail[want] <= j) want++;
        }
        if (want < need) want = need;
        if (want > before) credit -= 1.0;
        prog.e[j].y |= want;
        prog.e[j].t = (uint32_t)(t * tscale);
        if (mode[j] == 1) t += P.tW + (want == E ? P.tWR : 0);
        else if (mode[j] != 3) t += j == 0 ? P.tFirst : mode[j] == 2 ? P.tL2 : want == 0 ? P.tL0 : P.tL;
        if (want > before && mode[j] != 1) {
            const double f = mode[j] == 3 ? (want - E - 1) / (double)P.nF : (want - P.n1) / (double)(P.n2 - P.n1);
            const double c = f < 0 ? 0 : f > 1 ? 1 : f;
            t += want >= NBLK - P.nZ ? P.tZ : want >= NBLK - P.nE ? P.tE : mode[j] == 3 ? P.tF1 + c * (P.tF2 - P.tF1) : P.tS1 + c * (P.tS2 - P.tS1);
        }
    }
    return prog.e[0].x == enc_block(0) && prog.e[0].z == 0;
}

static const Plan kPlan = {5,5,6,14,150,840,102,1417,4,22,733,643,12,837,12,118,816,2600,0,608,152,20,1150,2,9,714,206,936,836,2,330,1900,2,
    {1,0,2},
    {1,6,4,0,7,9,13,3,12,8,5,10,2,11, 8,2,0,4,3,1,10,11,5,9,12,6,7,13, 11,10,12,0,1,2,13,3,4,5,6,7,8,9}};

constexpr int FB_BLOCKS = 1024;
__device__ float g_fb_part[FB_BLOCKS * C];
__device__ __nv_bfloat16 g_fb_s[C];
__global__ void fb_sum(const __nv_bfloat16* __restrict__ x, int rows) {
    for (int c = threadIdx.x; c < C; c += blockDim.x) {
        float a = 0.f;
        for (int r = blockIdx.x; r < rows; r += gridDim.x) a += __bfloat162float(x[(size_t)r * C + c]);
        g_fb_part[blockIdx.x * C + c] = a;
    }
}
__global__ void fb_gate(const __nv_bfloat16* __restrict__ w1d, int rows) {
    for (int c = threadIdx.x; c < C; c += blockDim.x) {
        float a = 0.f;
        for (int i = 0; i < FB_BLOCKS; i++) a += g_fb_part[i * C + c];
        g_fb_s[c] = gate(a, (float)rows, __bfloat162float(w1d[0]));
    }
}
__global__ void fb_scale(const __nv_bfloat16* __restrict__ x, __nv_bfloat16* __restrict__ out, size_t n) {
    for (size_t i = blockIdx.x * (size_t)blockDim.x + threadIdx.x; i < n; i += (size_t)gridDim.x * blockDim.x) out[i] = __hmul(x[i], g_fb_s[i % C]);
}

}

extern "C" void kernel_launch(void* const* d_in, const int* in_sizes, int n_in, void* d_out, int out_size) {
    using namespace eca;
    (void)n_in; (void)out_size;
    static int mode = -1;
    static Prog prog;
    if (mode < 0) {
        int dev = 0, sms = 0, occ = 0, coop = 0, khz = 0, bits = 0;
        cudaGetDevice(&dev);
        cudaDeviceGetAttribute(&sms, cudaDevAttrMultiProcessorCount, dev);
        cudaDeviceGetAttribute(&coop, cudaDevAttrCooperativeLaunch, dev);
        cudaDeviceGetAttribute(&khz, cudaDevAttrMemoryClockRate, dev);
        cudaDeviceGetAttribute(&bits, cudaDevAttrGlobalMemoryBusWidth, dev);
        double tscale = khz > 0 && bits > 0 ? 2619000.0 * 5120.0 / ((double)khz * bits) : 1.0;
        if (tscale < 0.5 || tscale > 2.0) tscale = 1.0;
        bool ok = cudaFuncSetAttribute(eca_kernel, cudaFuncAttributeMaxDynamicSharedMemorySize, SMEM_BYTES) == cudaSuccess;
        ok = ok && cudaOccupancyMaxActiveBlocksPerMultiprocessor(&occ, eca_kernel, 384, SMEM_BYTES) == cudaSuccess;
        ok = ok && coop && occ >= 1 && sms >= G && build_program(kPlan, prog, tscale);
        (void)cudaGetLastError();
        mode = ok ? 1 : 0;
    }
    const char* x = (const char*)d_in[0];
    const __nv_bfloat16* w = (const __nv_bfloat16*)d_in[1];
    char* out = (char*)d_out;
    if (mode == 1 && in_sizes[0] == HW * C && (((uintptr_t)x | (uintptr_t)out) & 15) == 0) {
        void* args[4] = {&x, &w, &out, &prog};
        cudaLaunchCooperativeKernel((const void*)eca_kernel, dim3(G), dim3(384), args, SMEM_BYTES, cudaStreamPerThread);
    } else {
        const int rows = in_sizes[0] / C;
        fb_sum<<<FB_BLOCKS, 384, 0, cudaStreamPerThread>>>((const __nv_bfloat16*)x, rows);
        fb_gate<<<1, 384, 0, cudaStreamPerThread>>>(w, rows);
        fb_scale<<<1024, 256, 0, cudaStreamPerThread>>>((const __nv_bfloat16*)x, (__nv_bfloat16*)out, (size_t)in_sizes[0]);
    }
}
```
